```python
import torch

def _softmax(x, axis=-1):
    return torch.softmax(x, dim=axis)
def _gelu(x):
    return torch.nn.functional.gelu(x, approximate="tanh")
def _silu(x):
    return torch.nn.functional.silu(x)
def _sigmoid(x):
    return torch.sigmoid(x)
def _layernorm(x, axis=-1, eps=1e-5):
    m = x.mean(dim=axis, keepdim=True)
    v = x.var(dim=axis, keepdim=True, unbiased=False)
    return (x - m) / torch.sqrt(v + eps)
def _scatter_add(tgt, idx, src, axis=0):
    return tgt.clone().index_add_(axis, idx, src)
def _segment_sum(src, seg, n):
    out = torch.zeros((n,) + src.shape[1:], dtype=src.dtype)
    return out.index_add_(0, seg, src)
def _pad(x, pw):
    flat = tuple(v for pair in reversed(pw) for v in pair)
    return torch.nn.functional.pad(x, flat)

kernel_name = 'recurrent_scan__sliding_block_cached__dense_activation_relu__decode'

def setup_inputs():

    _w = (lambda a: (lambda t: t.to(torch.bfloat16) if t.is_floating_point() else t)(torch.as_tensor(a)))
    def _A_setup():
        B, Sq, D = 4, 1, 512
        Hq, Hkv, Sk, Dh = 32, 8, 16384, 128
        assert Hq % Hkv == 0, (Hq, Hkv)
        return {
            "x": _w((lambda *s: torch.randn(*s, dtype=torch.bfloat16) * 0.05)(B, Sq, D)),
            "k_cache": _w((lambda *s: torch.randn(*s, dtype=torch.bfloat16) * 1.6)(B, Hkv, Sk, Dh)),
            "v_cache": _w((lambda *s: torch.randn(*s, dtype=torch.bfloat16) * 0.2)(B, Hkv, Sk, Dh)),
            "wq": _w((lambda *s: torch.randn(*s, dtype=torch.bfloat16) * 1.6)(D, Hq * Dh) * (D ** -0.5)),
            "wo": _w((lambda *s: torch.randn(*s, dtype=torch.bfloat16) * 0.2)(Hq * Dh, D) * ((Hq * Dh) ** -0.5)),
        }
    _A_in = _A_setup()

    def _B_setup():
        B, S, D, Dff = 4, 1, 512, 1792
        return {
            "x": _w((lambda *s: torch.randn(*s, dtype=torch.bfloat16) * 0.05)(B, S, D)),
            "w1": _w((lambda *s: torch.randn(*s, dtype=torch.bfloat16) * 0.1)(D, Dff)),
            "w2": _w((lambda *s: torch.randn(*s, dtype=torch.bfloat16) * 0.1)(Dff, D)),
        }
    _B_in = _B_setup()

    return {
        "A_x": _A_in["x"],
        "A_k_cache": _A_in["k_cache"],
        "A_v_cache": _A_in["v_cache"],
        "A_wq": _A_in["wq"],
        "A_wo": _A_in["wo"],
        "B_x": _B_in["x"],
        "B_w1": _B_in["w1"],
        "B_w2": _B_in["w2"],
    }

def reference(A_x, A_k_cache, A_v_cache, A_wq, A_wo, B_x, B_w1, B_w2):
    def _A_ref(x, k_cache, v_cache, wq, wo):
        B, Sq, D = x.shape
        Hq, Dh = 32, 128
        Hkv, Sk = k_cache.shape[1], k_cache.shape[2]
        W = min(4096, max(256, Sk // 4))
        rep = Hq // Hkv
        q = (lambda x, *d: x.permute(*d))((x @ wq).reshape(B, Sq, Hq, Dh), 0, 2, 1, 3)
        k = (lambda x, n, axis: torch.repeat_interleave(x, n, dim=axis))(k_cache[:, :, Sk - W:, :], rep, axis=1)
        v = (lambda x, n, axis: torch.repeat_interleave(x, n, dim=axis))(v_cache[:, :, Sk - W:, :], rep, axis=1)
        scores = torch.einsum("bhqd,bhkd->bhqk", q, k) * (Dh ** -0.5)
        p = _softmax(scores, axis=-1)
        o = torch.einsum("bhqk,bhkd->bhqd", p, v)
        return (lambda x, *d: x.permute(*d))(o, 0, 2, 1, 3).reshape(B, Sq, Hq * Dh) @ wo

    def _B_ref(x, w1, w2):
        h = torch.einsum("bsd,df->bsf", x, w1)
        zero = torch.zeros_like(h)
        h = torch.maximum(h, zero)
        return torch.einsum("bsf,fd->bsd", h, w2)

    x = A_x
    xn = _layernorm(x, axis=-1)
    s = _A_ref(xn, A_k_cache, A_v_cache, A_wq, A_wo)
    g = _silu(_B_ref(xn, B_w1, B_w2))
    return x + s * g
```

```cpp
#include <cuda_runtime.h>
#include <cuda_bf16.h>
#include <cuda.h>
#include <stdint.h>

namespace {

constexpr int NB = 4, DM = 512, HKV = 8, SK = 16384, DH = 128, WIN = 4096, DFF = 1792;
constexpr int NATT = 128, NFFN = 4, NCTA = NATT + NFFN;
constexpr int TILE_B = 8192;
constexpr int NKT = 32, NVT = 32, NWT = 4, NT = NKT + NVT;
#define NSLOT_ 21
#define WINDOW_ 5
constexpr int NSLOT = NSLOT_;
constexpr int WINDOW = WINDOW_;
constexpr int WINDOW0 = WINDOW < 6 ? WINDOW : 6;
#define PREW_AT_ 12
constexpr int PREW_AT = PREW_AT_;
constexpr int NTHREADS = 320;

constexpr int FSLOT_B = 32768, FNSLOT = 6, FN1 = 16, FN2 = 14, FW1_B = 7 * 4096;

constexpr int SM_W = NSLOT * TILE_B;
constexpr int SM_P = SM_W + 32768;
constexpr int SM_O = SM_P + 8192;
constexpr int SM_XN = SM_O + 1024;
constexpr int SM_RED = SM_XN + 4096;
constexpr int SM_Q = SM_RED + 4096;
constexpr int SM_MISC = SM_Q + 1024;
constexpr int SM_BAR = SM_MISC + 512;
constexpr int SM_TOTAL = SM_BAR + 8 * (NT + NWT + NSLOT + 8);
constexpr int SMEM_BYTES = SM_TOTAL + 1024;
static_assert(SM_P >= FNSLOT * FSLOT_B, "ring too small for FFN");
static_assert(WINDOW >= WINDOW0 && WINDOW <= NSLOT && SMEM_BYTES <= 232448 - 512, "config");

__device__ unsigned int g_epoch[NCTA];
__device__ __align__(128) unsigned long long g_q[NB * HKV * 256];
__device__ __align__(128) unsigned long long g_ml[NATT * 4 * 2];
__device__ __align__(128) unsigned long long g_o[32 * 4 * 4 * 128];
__device__ __align__(128) unsigned long long g_y[NB * 32 * 32 * 16];
__device__ __align__(128) unsigned long long g_f[NB * 32 * 4 * 16];
#define STAMP(i) do {} while (0)
#define DUMP(a, b) do {} while (0)

__device__ __forceinline__ uint32_t smem_u32(const void* p) { return (uint32_t)__cvta_generic_to_shared(p); }
__device__ __forceinline__ void mbar_init(uint32_t bar, uint32_t cnt) {
    asm volatile("mbarrier.init.shared::cta.b64 [%0], %1;" :: "r"(bar), "r"(cnt) : "memory");
}
__device__ __forceinline__ void mbar_expect_tx(uint32_t bar, uint32_t bytes) {
    asm volatile("mbarrier.arrive.expect_tx.shared::cta.b64 _, [%0], %1;" :: "r"(bar), "r"(bytes) : "memory");
}
__device__ __forceinline__ void mbar_arrive(uint32_t bar, uint32_t cnt) {
    asm volatile("mbarrier.arrive.shared::cta.b64 _, [%0], %1;" :: "r"(bar), "r"(cnt) : "memory");
}
__device__ __forceinline__ bool mbar_try(uint32_t bar, uint32_t parity) {
    uint32_t ok;
    asm volatile("{\n.reg .pred p;\nmbarrier.try_wait.parity.shared::cta.b64 p, [%1], %2;\nselp.u32 %0, 1, 0, p;\n}"
                 : "=r"(ok) : "r"(bar), "r"(parity) : "memory");
    return ok != 0;
}
constexpr uint32_t SPIN_LIMIT = 1u << 22;
__device__ __forceinline__ void mbar_wait(uint32_t bar, uint32_t parity) {
    uint32_t n = 0;
    while (!mbar_try(bar, parity)) {
        if (++n > SPIN_LIMIT) __trap();
    }
}
__device__ __forceinline__ bool mbar_test(uint32_t bar, uint32_t parity) {
    uint32_t ok;
    asm volatile("{\n.reg .pred p;\nmbarrier.test_wait.parity.shared::cta.b64 p, [%1], %2;\nselp.u32 %0, 1, 0, p;\n}"
                 : "=r"(ok) : "r"(bar), "r"(parity) : "memory");
    return ok != 0;
}
__device__ __forceinline__ bool elect_one() {
    uint32_t pred;
    asm volatile("{\n.reg .pred p;\nelect.sync _|p, 0xffffffff;\nselp.u32 %0, 1, 0, p;\n}" : "=r"(pred));
    return pred != 0;
}
__device__ __forceinline__ uint64_t policy_stream() {
    uint64_t p; asm volatile("createpolicy.fractional.L2::evict_first.b64 %0, 1.0;" : "=l"(p)); return p;
}
__device__ __forceinline__ float ex2(float x) { float y; asm("ex2.approx.ftz.f32 %0, %1;" : "=f"(y) : "f"(x)); return y; }
__device__ __forceinline__ float sqrt_fast(float x) { float y; asm("sqrt.approx.f32 %0, %1;" : "=f"(y) : "f"(x)); return y; }
__device__ __forceinline__ void bulk_g2s(uint32_t dst, const void* src, uint32_t bytes, uint32_t bar, uint64_t pol) {
    asm volatile("cp.async.bulk.shared::cluster.global.mbarrier::complete_tx::bytes.L2::cache_hint [%0], [%1], %2, [%3], %4;"
                 :: "r"(dst), "l"(src), "r"(bytes), "r"(bar), "l"(pol) : "memory");
}
__device__ __forceinline__ void tma_3d(uint32_t dst, const CUtensorMap* map, int c0, int c1, int c2, uint32_t bar, uint64_t pol) {
    asm volatile("cp.async.bulk.tensor.3d.shared::cluster.global.mbarrier::complete_tx::bytes.L2::cache_hint [%0], [%1, {%3, %4, %5}], [%2], %6;"
                 :: "r"(dst), "l"(map), "r"(bar), "r"(c0), "r"(c1), "r"(c2), "l"(pol) : "memory");
}
__device__ __forceinline__ void tma_2d(uint32_t dst, const CUtensorMap* map, int c0, int c1, uint32_t bar, uint64_t pol) {
    asm volatile("cp.async.bulk.tensor.2d.shared::cluster.global.mbarrier::complete_tx::bytes.L2::cache_hint [%0], [%1, {%3, %4}], [%2], %5;"
                 :: "r"(dst), "l"(map), "r"(bar), "r"(c0), "r"(c1), "l"(pol) : "memory");
}
__device__ __forceinline__ void prefetch_map(const CUtensorMap* map) {
    asm volatile("prefetch.tensormap [%0];" :: "l"(map) : "memory");
}
__device__ __forceinline__ void bar_sync(int id, int n) { asm volatile("bar.sync %0, %1;" :: "r"(id), "r"(n) : "memory"); }
__device__ __forceinline__ void bar_arrive(int id, int n) { asm volatile("bar.arrive %0, %1;" :: "r"(id), "r"(n) : "memory"); }

__device__ __forceinline__ uint4 lds128(uint32_t a) {
    uint4 v; asm volatile("ld.shared.v4.u32 {%0,%1,%2,%3}, [%4];" : "=r"(v.x), "=r"(v.y), "=r"(v.z), "=r"(v.w) : "r"(a) : "memory"); return v;
}
__device__ __forceinline__ float2 lds64f(uint32_t a) {
    float2 v; asm volatile("ld.shared.v2.f32 {%0,%1}, [%2];" : "=f"(v.x), "=f"(v.y) : "r"(a) : "memory"); return v;
}
__device__ __forceinline__ float4 lds128f(uint32_t a) {
    float4 v; asm volatile("ld.shared.v4.f32 {%0,%1,%2,%3}, [%4];" : "=f"(v.x), "=f"(v.y), "=f"(v.z), "=f"(v.w) : "r"(a) : "memory"); return v;
}
__device__ __forceinline__ uint32_t lds32(uint32_t a) {
    uint32_t v; asm volatile("ld.shared.u32 %0, [%1];" : "=r"(v) : "r"(a) : "memory"); return v;
}
__device__ __forceinline__ void sts32(uint32_t a, uint32_t v) { asm volatile("st.shared.u32 [%0], %1;" :: "r"(a), "r"(v) : "memory"); }
__device__ __forceinline__ void sts16(uint32_t a, uint16_t v) { asm volatile("st.shared.u16 [%0], %1;" :: "r"(a), "h"(v) : "memory"); }
__device__ __forceinline__ void sts64f(uint32_t a, float x, float y) { asm volatile("st.shared.v2.f32 [%0], {%1,%2};" :: "r"(a), "f"(x), "f"(y) : "memory"); }
__device__ __forceinline__ void sts128(uint32_t a, uint4 v) {
    asm volatile("st.shared.v4.u32 [%0], {%1,%2,%3,%4};" :: "r"(a), "r"(v.x), "r"(v.y), "r"(v.z), "r"(v.w) : "memory");
}
__device__ __forceinline__ void sts128f(uint32_t a, float x, float y, float z, float w) {
    asm volatile("st.shared.v4.f32 [%0], {%1,%2,%3,%4};" :: "r"(a), "f"(x), "f"(y), "f"(z), "f"(w) : "memory");
}
__device__ __forceinline__ uint4 ldsm_t(uint32_t a) {
    uint4 v;
    asm volatile("ldmatrix.sync.aligned.m8n8.x4.trans.shared.b16 {%0,%1,%2,%3}, [%4];"
                 : "=r"(v.x), "=r"(v.y), "=r"(v.z), "=r"(v.w) : "r"(a) : "memory");
    return v;
}
__device__ __forceinline__ void mma(float (&c)[4], uint32_t a0, uint32_t a1, uint32_t a2, uint32_t a3, uint32_t b0, uint32_t b1) {
    asm volatile("mma.sync.aligned.m16n8k16.row.col.f32.bf16.bf16.f32 {%0,%1,%2,%3}, {%4,%5,%6,%7}, {%8,%9}, {%0,%1,%2,%3};"
                 : "+f"(c[0]), "+f"(c[1]), "+f"(c[2]), "+f"(c[3])
                 : "r"(a0), "r"(a1), "r"(a2), "r"(a3), "r"(b0), "r"(b1));
}
__device__ __forceinline__ uint32_t pack_bf16(float lo, float hi) {
    uint32_t r; asm("cvt.rn.bf16x2.f32 %0, %1, %2;" : "=r"(r) : "f"(hi), "f"(lo)); return r;
}
__device__ __forceinline__ float rbf(float x) { return __bfloat162float(__float2bfloat16_rn(x)); }
__device__ __forceinline__ float bf_lo(uint32_t v) { return __uint_as_float(v << 16); }
__device__ __forceinline__ float bf_hi(uint32_t v) { return __uint_as_float(v & 0xffff0000u); }
__device__ __forceinline__ uint16_t bf_bits(float x) { return __bfloat16_as_ushort(__float2bfloat16_rn(x)); }

__device__ __forceinline__ void ll_st1(unsigned long long* p, uint32_t v, uint32_t tag) {
    asm volatile("{\n.reg .b64 a;\nmov.b64 a, {%1, %2};\nst.relaxed.gpu.global.b64 [%0], a;\n}" :: "l"(p), "r"(v), "r"(tag) : "memory");
}
__device__ __forceinline__ void ll_st2(unsigned long long* p, float v0, float v1, uint32_t tag) {
    asm volatile("{\n.reg .b64 a, b;\nmov.b64 a, {%1, %3};\nmov.b64 b, {%2, %3};\nst.relaxed.gpu.global.v2.b64 [%0], {a, b};\n}"
                 :: "l"(p), "r"(__float_as_uint(v0)), "r"(__float_as_uint(v1)), "r"(tag) : "memory");
}
__device__ __forceinline__ uint2 ll_ld1(const unsigned long long* p) {
    uint2 v;
    asm volatile("{\n.reg .b64 a;\nld.relaxed.gpu.global.b64 a, [%2];\nmov.b64 {%0, %1}, a;\n}" : "=r"(v.x), "=r"(v.y) : "l"(p) : "memory");
    return v;
}
__device__ __forceinline__ uint4 ll_ld2(const unsigned long long* p) {
    uint4 v;
    asm volatile("{\n.reg .b64 a, b;\nld.relaxed.gpu.global.v2.b64 {a, b}, [%4];\nmov.b64 {%0, %1}, a;\nmov.b64 {%2, %3}, b;\n}"
                 : "=r"(v.x), "=r"(v.y), "=r"(v.z), "=r"(v.w) : "l"(p) : "memory");
    return v;
}
__device__ __forceinline__ uint2 ldg64_nc(const void* p) {
    uint2 v; asm volatile("ld.global.nc.L1::no_allocate.L2::256B.v2.u32 {%0,%1}, [%2];" : "=r"(v.x), "=r"(v.y) : "l"(p)); return v;
}
__device__ __forceinline__ uint4 ldg128_nc(const void* p) {
    uint4 v; asm volatile("ld.global.nc.v4.u32 {%0,%1,%2,%3}, [%4];" : "=r"(v.x), "=r"(v.y), "=r"(v.z), "=r"(v.w) : "l"(p)); return v;
}
__device__ __forceinline__ float warp_sum(float v) {
#pragma unroll
    for (int o = 16; o; o >>= 1) v += __shfl_xor_sync(0xffffffffu, v, o);
    return v;
}

__device__ __forceinline__ void layernorm_row(const uint4 xa, const uint4 xb, int b, int lane, uint32_t sxn) {
    float v[16];
    v[0] = bf_lo(xa.x); v[1] = bf_hi(xa.x); v[2] = bf_lo(xa.y); v[3] = bf_hi(xa.y);
    v[4] = bf_lo(xa.z); v[5] = bf_hi(xa.z); v[6] = bf_lo(xa.w); v[7] = bf_hi(xa.w);
    v[8] = bf_lo(xb.x); v[9] = bf_hi(xb.x); v[10] = bf_lo(xb.y); v[11] = bf_hi(xb.y);
    v[12] = bf_lo(xb.z); v[13] = bf_hi(xb.z); v[14] = bf_lo(xb.w); v[15] = bf_hi(xb.w);
    float s = 0.f;
#pragma unroll
    for (int i = 0; i < 16; i++) s += v[i];
    const float mean = warp_sum(s) * (1.0f / DM);
    float q = 0.f;
#pragma unroll
    for (int i = 0; i < 16; i++) { const float d = v[i] - mean; q += d * d; }
    const float var = warp_sum(q) * (1.0f / DM);
    const float mb = rbf(mean);
    const float rs = __fdividef(1.0f, rbf(sqrt_fast(rbf(rbf(var) + 1e-5f))));
#pragma unroll
    for (int hlf = 0; hlf < 2; hlf++) {
        const uint32_t base = sxn + (hlf * 8 + (lane >> 2)) * 256 + b * 64 + (lane & 3) * 4;
#pragma unroll
        for (int i = 0; i < 4; i++) {
            const float lo = rbf(v[hlf * 8 + 2 * i] - mb) * rs;
            const float hi = rbf(v[hlf * 8 + 2 * i + 1] - mb) * rs;
            sts32(base + i * 16, pack_bf16(lo, hi));
        }
    }
}

struct Params {
    const __nv_bfloat16* x;
    const __nv_bfloat16* k;
    __nv_bfloat16* out;
};

__global__ void __launch_bounds__(NTHREADS, 1)
fused_decode_kernel(const Params p, const __grid_constant__ CUtensorMap map_wq,
                    const __grid_constant__ CUtensorMap map_v, const __grid_constant__ CUtensorMap map_wo,
                    const __grid_constant__ CUtensorMap map_w1, const __grid_constant__ CUtensorMap map_w2) {
    extern __shared__ uint8_t smem_raw[];
    const uint32_t sb = (smem_u32(smem_raw) + 1023u) & ~1023u;
    const int tid = threadIdx.x, lane = tid & 31;
    const int warp = __shfl_sync(0xffffffffu, tid >> 5, 0);
    const int cta = blockIdx.x;
    const bool att = cta < NATT;
    const uint32_t s_full = sb + SM_BAR, s_empty = s_full + 8 * (NT + NWT), s_wrdy = s_empty + 8 * NSLOT, s_kd = s_wrdy + 8, s_vd = s_wrdy + 16;
    const uint32_t s_wo = s_full + 8 * NT, s_wq = s_wrdy + 24;
    const int kvh = cta >> 4, r = cta & 15, b = r >> 2, j = r & 3;
    const char* kbase = (const char*)p.k + ((size_t)(b * HKV + kvh) * SK + (SK - WIN)) * DH * 2 + (size_t)j * TILE_B;

    if (tid == 0) STAMP(0);
    if (att && warp < 8) {
        if (elect_one()) {
            const uint64_t pol = policy_stream();
            if (warp == 2 || warp == 3) {
                const uint32_t bar = s_wq + 8 * (warp - 2);
                mbar_init(bar, 1);
                mbar_expect_tx(bar, 16384);
                tma_2d(sb + SM_W + (warp - 2) * 16384, &map_wq, cta * 32, (warp - 2) * 256, bar, pol);
            } else if (warp < WINDOW0 + 2) {
                const int kt = warp < 2 ? warp : warp - 2;
                mbar_init(s_full + 8 * kt, 1);
                mbar_expect_tx(s_full + 8 * kt, TILE_B);
                bulk_g2s(sb + kt * TILE_B, kbase + (size_t)kt * 4 * TILE_B, TILE_B, s_full + 8 * kt, pol);
            }
        }
        __syncwarp();
    }
    if (att && warp < 8) bar_arrive(3, 320);
    if (tid == 0) STAMP(1);

    const uint32_t s_tag = sb + SM_MISC + 384;
    const int g = lane >> 2, t = lane & 3;
    const int bsel = ((t & 1) << 1) | (t >> 1);
    const bool lo = t < 2;
    const int lrow = (lane & 7) + ((lane >> 4) << 3);
    const int lchk = (lane >> 3) & 1;
    const uint32_t boff = (g & 3) * 64 + t * 16;
    const float L2E = 1.4426950408889634f;

    if (warp < 8) {
        if (warp < NB) {
            const uint4 xa = ldg128_nc(p.x + warp * DM + lane * 8);
            const uint4 xb = ldg128_nc(p.x + warp * DM + 256 + lane * 8);
            layernorm_row(xa, xb, warp, lane, sb + SM_XN);
        }
        if (tid == 0) STAMP(2);
        bar_sync(1, NTHREADS);
        const uint32_t tag = lds32(s_tag);
        if (tid == 0) STAMP(3);
        if (att) {
            {
                float c0[4] = {0.f, 0.f, 0.f, 0.f}, c1[4] = {0.f, 0.f, 0.f, 0.f};
                const uint32_t xa = sb + SM_XN + warp * 512 + boff;
                const uint4 b0 = lds128(xa), b1 = lds128(xa + 256);
                const uint32_t bb[8] = {b0.x, b0.y, b0.z, b0.w, b1.x, b1.y, b1.z, b1.w};
                const uint32_t wa = sb + SM_W + (warp * 64 + lrow) * 64;
                const uint32_t sw = (lrow >> 1) & 3;
                mbar_wait(s_wq + 8 * (warp >> 2), 0);
#pragma unroll
                for (int ks = 0; ks < 4; ks++) {
                    const uint4 v0 = ldsm_t(wa + ks * 1024 + ((lchk ^ sw) << 4)), v1 = ldsm_t(wa + ks * 1024 + (((2 + lchk) ^ sw) << 4));
                    mma(c0, v0.x, v0.y, v0.z, v0.w, bb[2 * ks], bb[2 * ks + 1]);
                    mma(c1, v1.x, v1.y, v1.z, v1.w, bb[2 * ks], bb[2 * ks + 1]);
                }
                sts128f(sb + SM_RED + warp * 512 + bsel * 128 + g * 16,
                        lo ? c0[0] : c0[1], lo ? c0[2] : c0[3], lo ? c1[0] : c1[1], lo ? c1[2] : c1[3]);
            }
            bar_sync(2, 256);
            if (tid < 64) {
                float s0 = 0.f, s1 = 0.f;
#pragma unroll
                for (int w = 0; w < 8; w++) { const float2 v = lds64f(sb + SM_RED + w * 512 + tid * 8); s0 += v.x; s1 += v.y; }
                ll_st1(g_q + ((tid >> 4) * HKV + kvh) * 256 + r * 16 + (tid & 15), pack_bf16(s0, s1), tag);
            }
            if (tid == 0) STAMP(4);
            {
                const unsigned long long* src = g_q + (b * HKV + kvh) * 256 + tid;
                uint2 v = ll_ld1(src);
                uint32_t n = 0;
                while (v.y != tag) {
                    __nanosleep(40);
                    if (++n > SPIN_LIMIT) __trap();
                    v = ll_ld1(src);
                }
                const uint32_t qa = sb + SM_Q + ((tid >> 4) * 32 + (tid & 1) * 16 + ((tid & 15) >> 1)) * 2;
                sts16(qa, (uint16_t)(v.x & 0xffffu));
                sts16(qa + 16, (uint16_t)(v.x >> 16));
            }
            bar_sync(2, 256);
            if (tid == 0) STAMP(5);
            {
                uint4 qb[4];
#pragma unroll
                for (int c = 0; c < 4; c++) qb[c] = lds128(sb + SM_Q + (g & 3) * 256 + (4 * (c ^ (g >> 2)) + t) * 16);
                const uint32_t koff = (2 * g) * 256 + t * 16;
                const bool valid = (g & 1) == (t >> 1);
                const uint32_t pa = sb + SM_P + (t & 1) * 128 + (g & 3) * 16 + (g >> 2) * 4;
                float mA = -INFINITY, mB = -INFINITY;
#pragma unroll 1
                for (int tt = warp; tt < NKT; tt += 8) {
                    const int slot = tt >= NSLOT ? tt - NSLOT : tt;
                    mbar_wait(s_full + 8 * tt, 0);
                    const uint32_t ka = sb + slot * TILE_B + koff;
                    float sc[2][4] = {{0.f, 0.f, 0.f, 0.f}, {0.f, 0.f, 0.f, 0.f}};
#pragma unroll
                    for (int c = 0; c < 4; c++) {
#pragma unroll
                        for (int mt = 0; mt < 2; mt++) {
                            const uint32_t a = ka + mt * 4096 + ((c ^ (g & 1)) << 6);
                            const uint4 x = lds128(a), y = lds128(a + 256);
                            mma(sc[mt], x.x, y.x, x.y, y.y, qb[c].x, qb[c].y);
                            mma(sc[mt], x.z, y.z, x.w, y.w, qb[c].z, qb[c].w);
                        }
                    }
                    __syncwarp();
                    if (lane == 0) mbar_arrive(s_empty + 8 * slot, 8);
                    if (valid) {
#pragma unroll
                        for (int mt = 0; mt < 2; mt++) {
                            const uint32_t ra = pack_bf16(sc[mt][0], sc[mt][2]), rb = pack_bf16(sc[mt][1], sc[mt][3]);
                            const float SC = 0.08838834764831845f;
                            const uint32_t sa = pack_bf16(bf_lo(ra) * SC, bf_hi(ra) * SC), sbb = pack_bf16(bf_lo(rb) * SC, bf_hi(rb) * SC);
                            mA = fmaxf(mA, fmaxf(bf_lo(sa), bf_hi(sa)));
                            mB = fmaxf(mB, fmaxf(bf_lo(sbb), bf_hi(sbb)));
                            sts32(pa + tt * 256 + mt * 8, sa);
                            sts32(pa + tt * 256 + mt * 8 + 64, sbb);
                        }
                    }
                }
#pragma unroll
                for (int o = 2; o <= 16; o <<= 1) {
                    mA = fmaxf(mA, __shfl_xor_sync(0xffffffffu, mA, o));
                    mB = fmaxf(mB, __shfl_xor_sync(0xffffffffu, mB, o));
                }
                if (lane < 2) { sts32(sb + SM_MISC + lane * 64 + warp * 4, __float_as_uint(mA)); sts32(sb + SM_MISC + lane * 64 + 32 + warp * 4, __float_as_uint(mB)); }
            }
            if (tid == 0) STAMP(6);
            bar_sync(2, 256);
            {
                const float4 m0 = lds128f(sb + SM_MISC + (g & 3) * 32), m1 = lds128f(sb + SM_MISC + (g & 3) * 32 + 16);
                const float m = fmaxf(fmaxf(fmaxf(m0.x, m0.y), fmaxf(m0.z, m0.w)), fmaxf(fmaxf(m1.x, m1.y), fmaxf(m1.z, m1.w)));
                float l = 0.f;
#pragma unroll
                for (int hf = 0; hf < 2; hf++) {
                    const uint32_t a = sb + SM_P + hf * 4096 + tid * 16;
                    const uint4 v = lds128(a);
                    uint32_t w[4] = {v.x, v.y, v.z, v.w};
#pragma unroll
                    for (int e = 0; e < 4; e++) {
                        const float p0 = ex2((bf_lo(w[e]) - m) * L2E), p1 = ex2((bf_hi(w[e]) - m) * L2E);
                        l += p0 + p1;
                        w[e] = pack_bf16(p0, p1);
                    }
                    sts128(a, make_uint4(w[0], w[1], w[2], w[3]));
                }
                l += __shfl_xor_sync(0xffffffffu, l, 1);
                l += __shfl_xor_sync(0xffffffffu, l, 2);
                l += __shfl_xor_sync(0xffffffffu, l, 16);
                if (lane < 16 && t == 0) sts32(sb + SM_MISC + 128 + g * 32 + warp * 4, __float_as_uint(l));
                bar_sync(2, 256);
                if (tid < 16 && t == 0) {
                    const float4 l0 = lds128f(sb + SM_MISC + 128 + g * 32), l1 = lds128f(sb + SM_MISC + 128 + g * 32 + 16);
                    ll_st2(g_ml + (cta * 4 + g) * 2, m, ((l0.x + l0.y) + (l0.z + l0.w)) + ((l1.x + l1.y) + (l1.z + l1.w)), tag);
                    if (tid == 0) mbar_arrive(s_kd, 1);
                }
            }
            const uint32_t aoff = (warp >> 2) * 4096 + lrow * 128 + ((((warp & 3) * 2 + lchk) ^ (lrow & 7)) << 4);
            unsigned long long* const o_dst = g_o + (((kvh * 4 + bsel) * 4 + j) * 4 + b) * 128 + warp * 16 + g * 2;
            unsigned long long* const y_dst = g_y + (size_t)((bsel * 32 + (cta & 3) * 8 + warp) * 32 + (cta >> 2)) * 16 + g * 2;
            float4 wj = make_float4(0.f, 0.f, 0.f, 0.f);
            {
                float a0[4] = {0.f, 0.f, 0.f, 0.f}, a1[4] = {0.f, 0.f, 0.f, 0.f};
                int slot = NKT % NSLOT;
#pragma unroll 1
                for (int i = 0; i < NVT; i++) {
                    const uint4 pb = lds128(sb + SM_P + i * 256 + boff);
                    if (i == PREW_AT) {
                        ll_st2(o_dst, 0.f, 0.f, 0u);
                        ll_st2(y_dst, 0.f, 0.f, 0u);
                    }
                    if (i == NVT - 2) {
                        mbar_wait(s_wrdy, 0);
                        wj = lds128f(sb + SM_MISC + 256 + (tid >> 6) * 16);
                    }
                    mbar_wait(s_full + 8 * (NKT + i), 0);
                    const uint32_t va = sb + slot * TILE_B + aoff;
                    const uint4 v0 = ldsm_t(va), v1 = ldsm_t(va + 2048);
                    mma(a0, v0.x, v0.y, v0.z, v0.w, pb.x, pb.y);
                    mma(a1, v1.x, v1.y, v1.z, v1.w, pb.z, pb.w);
                    if (i + NKT + NSLOT < NT) {
                        __syncwarp();
                        if (lane == 0) mbar_arrive(s_empty + 8 * slot, 1);
                    }
                    if (++slot == NSLOT) slot = 0;
                }
                if (tid == 0) STAMP(7);
                ll_st2(o_dst, lo ? a0[0] + a1[0] : a0[1] + a1[1], lo ? a0[2] + a1[2] : a0[3] + a1[3], tag);
                if (tid == 0) mbar_arrive(s_vd, 1);
            }
            {
                const unsigned long long* src = g_o + (size_t)(cta >> 2) * 2048 + tid * 2;
                uint4 v[4];
                uint32_t n = 0;
                while (true) {
#pragma unroll
                    for (int i = 0; i < 4; i++) v[i] = ll_ld2(src + i * 512);
                    bool ok = true;
#pragma unroll
                    for (int i = 0; i < 4; i++) ok = ok && v[i].y == tag && v[i].w == tag;
                    if (ok) break;
                    if (++n > SPIN_LIMIT) __trap();
                }
                const float o0 = wj.x * __uint_as_float(v[0].x) + wj.y * __uint_as_float(v[1].x) + wj.z * __uint_as_float(v[2].x) + wj.w * __uint_as_float(v[3].x);
                const float o1 = wj.x * __uint_as_float(v[0].z) + wj.y * __uint_as_float(v[1].z) + wj.z * __uint_as_float(v[2].z) + wj.w * __uint_as_float(v[3].z);
                const int dp = tid & 63, w2 = dp >> 3, gg = dp & 7;
                const uint32_t oa = sb + SM_O + (w2 >> 1) * 256 + (tid >> 6) * 64 + (gg >> 1) * 16 + (w2 & 1) * 8 + (gg & 1) * 2;
                sts16(oa, bf_bits(o0));
                sts16(oa + 4, bf_bits(o1));
            }
            if (tid == 0) STAMP(8);
            {
                uint4 wa[8];
#pragma unroll
                for (int i = 0; i < NWT; i++) {
                    mbar_wait(s_wo + 8 * i, 0);
                    const uint32_t va = sb + SM_W + i * TILE_B + aoff;
                    wa[2 * i] = ldsm_t(va); wa[2 * i + 1] = ldsm_t(va + 2048);
                }
                if (tid == 0) STAMP(10);
                bar_sync(2, 256);
                float c[4][4];
#pragma unroll
                for (int i = 0; i < NWT; i++) {
                    const uint4 ob = lds128(sb + SM_O + i * 256 + boff);
                    c[i][0] = c[i][1] = c[i][2] = c[i][3] = 0.f;
                    mma(c[i], wa[2 * i].x, wa[2 * i].y, wa[2 * i].z, wa[2 * i].w, ob.x, ob.y);
                    mma(c[i], wa[2 * i + 1].x, wa[2 * i + 1].y, wa[2 * i + 1].z, wa[2 * i + 1].w, ob.z, ob.w);
                }
                const float y0 = lo ? (c[0][0] + c[1][0]) + (c[2][0] + c[3][0]) : (c[0][1] + c[1][1]) + (c[2][1] + c[3][1]);
                const float y1 = lo ? (c[0][2] + c[1][2]) + (c[2][2] + c[3][2]) : (c[0][3] + c[1][3]) + (c[2][3] + c[3][3]);
                ll_st2(y_dst, y0, y1, tag);
            }
            if (tid == 0) { STAMP(9); DUMP(0, 11); }
        } else {
            const int f = cta - NATT;
            const uint32_t arow = warp * 4096 + lrow * 128;
            unsigned long long* const f_dst = g_f + ((bsel * 32 + warp * 4) * 4 + f) * 16 + g * 2;
#pragma unroll
            for (int i = 0; i < 4; i++) ll_st2(f_dst + i * 64, 0.f, 0.f, 0u);
            float c[4][4];
            int slot = 0, ph = 0;
#pragma unroll
            for (int i = 0; i < 4; i++) c[i][0] = c[i][1] = c[i][2] = c[i][3] = 0.f;
#pragma unroll 1
            for (int tt = 0; tt < FN1 + FN2; tt++) {
                if (tt == FN1) {
                    if (warp < 7) {
#pragma unroll
                        for (int i = 0; i < 4; i++) {
                            const float h0 = fmaxf(lo ? c[i][0] : c[i][1], 0.f), h1 = fmaxf(lo ? c[i][2] : c[i][3], 0.f);
                            const uint32_t ha = sb + SM_RED + (2 * warp + (i >> 1)) * 256 + bsel * 64 + (g >> 1) * 16 + (i & 1) * 8 + (g & 1) * 2;
                            sts16(ha, bf_bits(h0));
                            sts16(ha + 4, bf_bits(h1));
                        }
                    }
#pragma unroll
                    for (int i = 0; i < 4; i++) c[i][0] = c[i][1] = c[i][2] = c[i][3] = 0.f;
                    bar_sync(2, 256);
                    if (tid == 0) STAMP(6);
                }
                const uint4 bb = lds128(sb + SM_XN + tt * 256 + boff);
                mbar_wait(s_full + 8 * slot, ph);
                if (tt >= FN1 || warp < 7) {
                    const uint32_t va = sb + slot * FSLOT_B + arow;
#pragma unroll
                    for (int i = 0; i < 4; i++) {
                        const uint32_t sw = ((2 * i + lchk) ^ (lrow & 7)) << 4;
                        const uint4 v0 = ldsm_t(va + sw), v1 = ldsm_t(va + sw + 2048);
                        mma(c[i], v0.x, v0.y, v0.z, v0.w, bb.x, bb.y);
                        mma(c[i], v1.x, v1.y, v1.z, v1.w, bb.z, bb.w);
                    }
                }
                __syncwarp();
                if (lane == 0) mbar_arrive(s_empty + 8 * slot, 1);
                if (++slot == FNSLOT) { slot = 0; ph ^= 1; }
            }
#pragma unroll
            for (int i = 0; i < 4; i++) ll_st2(f_dst + i * 64, lo ? c[i][0] : c[i][1], lo ? c[i][2] : c[i][3], tag);
            if (tid == 0) { STAMP(9); DUMP(0, 11); }
        }
    } else if (warp == 8) {
        const bool leader = elect_one();
        const uint64_t pol = policy_stream();
        if (att) {
            if (leader) {
                STAMP(16);
#pragma unroll
                for (int i = WINDOW0; i < WINDOW; i++) mbar_init(s_full + 8 * i, 1);
#pragma unroll
                for (int i = WINDOW0; i < WINDOW; i++) {
                    mbar_expect_tx(s_full + 8 * i, TILE_B);
                    bulk_g2s(sb + i * TILE_B, kbase + (size_t)i * 4 * TILE_B, TILE_B, s_full + 8 * i, pol);
                }
#pragma unroll
                for (int i = WINDOW; i < NT + NWT; i++) mbar_init(s_full + 8 * i, 1);
                prefetch_map(&map_v); prefetch_map(&map_wo);
            }
            __syncwarp();
            bar_sync(3, 320);
            bar_arrive(1, NTHREADS);
            if (leader) STAMP(17);
            const int vrow0 = (b * HKV + kvh) * SK + (SK - WIN) + j * 32;
            int slot = WINDOW % NSLOT, ph = (WINDOW / NSLOT) & 1;
            int watch = lane < WINDOW ? lane : -1;
            int next = WINDOW;
            uint32_t spins = 0;
            while (next < NT + NWT) {
                const bool done = watch >= 0 && mbar_test(s_full + 8 * watch, 0);
                uint32_t mask = __ballot_sync(0xffffffffu, done);
                if (++spins > (SPIN_LIMIT << 4)) __trap();
                while (mask != 0 && next < NT + NWT) {
                    const int l = __ffs(mask) - 1;
                    mask &= mask - 1;
                    const uint32_t bar = s_full + 8 * next;
                    if (next == WINDOW && leader) STAMP(19);
                    if (next == NKT && leader) STAMP(20);
                    if (next < NT) {
                        if (next >= NSLOT) mbar_wait(s_empty + 8 * slot, ph ^ 1);
                        if (leader) {
                            const uint32_t dst = sb + slot * TILE_B;
                            mbar_expect_tx(bar, TILE_B);
                            if (next < NKT) bulk_g2s(dst, kbase + (size_t)next * 4 * TILE_B, TILE_B, bar, pol);
                            else tma_3d(dst, &map_v, 0, vrow0 + (next - NKT) * 128, 0, bar, pol);
                        }
                    } else if (leader) {
                        mbar_expect_tx(bar, TILE_B);
                        tma_3d(sb + SM_W + (next - NT) * TILE_B, &map_wo, 0, (cta >> 2) * 128 + (next - NT) * 32, (cta & 3) * 2, bar, pol);
                    }
                    __syncwarp();
                    if (lane == l) watch = next;
                    next++;
                    if (++slot == NSLOT) { slot = 0; ph ^= 1; }
                }
            }
            if (leader) { STAMP(18); DUMP(16, 21); }
        } else {
            const int f = cta - NATT;
            if (leader) {
                STAMP(16);
#pragma unroll
                for (int i = 0; i < FNSLOT; i++) { mbar_init(s_full + 8 * i, 1); mbar_init(s_empty + 8 * i, 8); }
            }
            __syncwarp();
            bar_arrive(1, NTHREADS);
            if (leader) {
                prefetch_map(&map_w2);
                int slot = 0, ph = 0;
#pragma unroll 1
                for (int tt = 0; tt < FN1 + FN2; tt++) {
                    if (tt >= FNSLOT) mbar_wait(s_empty + 8 * slot, ph ^ 1);
                    const uint32_t dst = sb + slot * FSLOT_B, bar = s_full + 8 * slot;
                    if (tt < FN1) { mbar_expect_tx(bar, FW1_B); tma_3d(dst, &map_w1, 0, tt * 32, f * 7, bar, pol); }
                    else { mbar_expect_tx(bar, FSLOT_B); tma_3d(dst, &map_w2, 0, f * 448 + (tt - FN1) * 32, 0, bar, pol); }
                    if (++slot == FNSLOT) { slot = 0; ph ^= 1; }
                }
                STAMP(18); DUMP(16, 21);
            }
        }
    } else {
        uint32_t tag = 0;
        if (lane == 0) STAMP(24);
        if (att) {
            if (elect_one()) {
#pragma unroll
                for (int i = 0; i < NSLOT; i++) mbar_init(s_empty + 8 * i, 8);
#pragma unroll
                for (int i = 0; i < 3; i++) mbar_init(s_wrdy + 8 * i, 1);
            }
            __syncwarp();
            bar_arrive(3, 320);
        }
        if (lane == 0) tag = *(volatile unsigned int*)&g_epoch[cta] + 1u;
        if (att) {
            ll_st2(g_q + ((lane >> 3) * HKV + kvh) * 256 + r * 16 + (lane & 7) * 2, 0.f, 0.f, 0u);
            if (lane < 4) ll_st2(g_ml + (cta * 4 + lane) * 2, 0.f, 0.f, 0u);
            __threadfence_block();
        }
        if (lane == 0) {
            if (tag == 0) tag = 1;
            *(volatile unsigned int*)&g_epoch[cta] = tag;
            sts32(s_tag, tag);
        }
        tag = __shfl_sync(0xffffffffu, tag, 0);
        if (lane == 0) STAMP(25);
        if (!att) { bar_arrive(1, NTHREADS); return; }
        const int rb = cta >> 5, cg = cta & 31;
        const float xres = __bfloat162float(p.x[rb * DM + cg * 16 + (lane & 15)]);
        bar_sync(1, NTHREADS);
        uint32_t n = 0;
        {
            const unsigned long long* src = g_ml + ((kvh * 16 + (lane & 15)) * 4 + ((cta >> 2) & 3)) * 2;
            mbar_wait(s_kd, 0);
            uint4 v = ll_ld2(src);
            while (!__all_sync(0xffffffffu, v.y == tag && v.w == tag)) {
                __nanosleep(200);
                if (++n > SPIN_LIMIT) __trap();
                v = ll_ld2(src);
            }
            const float m = __uint_as_float(v.x), l = __uint_as_float(v.z);
            float mm = fmaxf(m, __shfl_xor_sync(0xffffffffu, m, 1));
            mm = fmaxf(mm, __shfl_xor_sync(0xffffffffu, mm, 2));
            const float e = ex2((m - mm) * L2E);
            float ll = e * l;
            ll += __shfl_xor_sync(0xffffffffu, ll, 1);
            ll += __shfl_xor_sync(0xffffffffu, ll, 2);
            if (lane < 16) sts32(sb + SM_MISC + 256 + lane * 4, __float_as_uint(__fdividef(e, ll)));
            __syncwarp();
            if (lane == 0) { mbar_arrive(s_wrdy, 1); STAMP(26); }
        }
        float gate;
        {
            const unsigned long long* src = g_f + ((rb * 32 + cg) * 4) * 16 + lane * 2;
            uint4 v = ll_ld2(src);
            while (!__all_sync(0xffffffffu, v.y == tag && v.w == tag)) {
                __nanosleep(200);
                if (++n > SPIN_LIMIT) __trap();
                v = ll_ld2(src);
            }
            float f0 = __uint_as_float(v.x), f1 = __uint_as_float(v.z);
            f0 += __shfl_xor_sync(0xffffffffu, f0, 8);  f1 += __shfl_xor_sync(0xffffffffu, f1, 8);
            f0 += __shfl_xor_sync(0xffffffffu, f0, 16); f1 += __shfl_xor_sync(0xffffffffu, f1, 16);
            const float f = rbf((lane & 8) ? f1 : f0);
            gate = rbf(f / (1.0f + ex2(-f * L2E)));
            if (lane == 0) STAMP(27);
        }
        mbar_wait(s_vd, 0);
        const unsigned long long* src = g_y + (size_t)(rb * 32 + cg) * 512 + lane * 2;
        float y0, y1;
        while (true) {
            uint4 v[8];
#pragma unroll
            for (int i = 0; i < 8; i++) v[i] = ll_ld2(src + i * 64);
            bool ok = true;
            y0 = 0.f; y1 = 0.f;
#pragma unroll
            for (int i = 0; i < 8; i++) {
                ok = ok && v[i].y == tag && v[i].w == tag;
                y0 += __uint_as_float(v[i].x); y1 += __uint_as_float(v[i].z);
            }
            if (__all_sync(0xffffffffu, ok)) break;
            if (++n > SPIN_LIMIT) __trap();
        }
        y0 += __shfl_xor_sync(0xffffffffu, y0, 8);  y1 += __shfl_xor_sync(0xffffffffu, y1, 8);
        y0 += __shfl_xor_sync(0xffffffffu, y0, 16); y1 += __shfl_xor_sync(0xffffffffu, y1, 16);
        const float s = rbf((lane & 8) ? y1 : y0);
        if (lane < 16) p.out[rb * DM + cg * 16 + lane] = __float2bfloat16_rn(xres + rbf(s * gate));
        if (lane == 0) { STAMP(28); DUMP(24, 29); }
    }
}

typedef CUresult (*EncodeTiledFn)(CUtensorMap*, CUtensorMapDataType, cuuint32_t, void*, const cuuint64_t*, const cuuint64_t*,
                                  const cuuint32_t*, const cuuint32_t*, CUtensorMapInterleave, CUtensorMapSwizzle,
                                  CUtensorMapL2promotion, CUtensorMapFloatOOBfill);

CUtensorMap make_map(EncodeTiledFn enc, const void* base, uint64_t rows, uint64_t cols, uint32_t nblk) {
    CUtensorMap m;
    cuuint64_t gd[3] = {64, rows, cols / 64};
    cuuint64_t gs[2] = {cols * 2, 128};
    cuuint32_t bd[3] = {64, 32, nblk};
    cuuint32_t es[3] = {1, 1, 1};
    enc(&m, CU_TENSOR_MAP_DATA_TYPE_BFLOAT16, 3, const_cast<void*>(base), gd, gs, bd, es, CU_TENSOR_MAP_INTERLEAVE_NONE,
        CU_TENSOR_MAP_SWIZZLE_128B, CU_TENSOR_MAP_L2_PROMOTION_L2_256B, CU_TENSOR_MAP_FLOAT_OOB_FILL_NONE);
    return m;
}

}

extern "C" void kernel_launch(void* const* d_in, const int* in_sizes, int n_in, void* d_out, int out_size) {
    (void)in_sizes; (void)n_in; (void)out_size;
    static EncodeTiledFn enc = nullptr;
    if (!enc) {
        void* fn = nullptr;
        cudaDriverEntryPointQueryResult st;
        cudaGetDriverEntryPoint("cuTensorMapEncodeTiled", &fn, cudaEnableDefault, &st);
        enc = (EncodeTiledFn)fn;
        cudaFuncSetAttribute(fused_decode_kernel, cudaFuncAttributeMaxDynamicSharedMemorySize, SMEM_BYTES);
    }
    Params p;
    p.x = (const __nv_bfloat16*)d_in[0];
    p.k = (const __nv_bfloat16*)d_in[1];
    p.out = (__nv_bfloat16*)d_out;
    CUtensorMap mwq;
    {
        cuuint64_t gd[2] = {4096, DM};
        cuuint64_t gs[1] = {4096 * 2};
        cuuint32_t bd[2] = {32, 256};
        cuuint32_t es[2] = {1, 1};
        enc(&mwq, CU_TENSOR_MAP_DATA_TYPE_BFLOAT16, 2, d_in[3], gd, gs, bd, es, CU_TENSOR_MAP_INTERLEAVE_NONE,
            CU_TENSOR_MAP_SWIZZLE_64B, CU_TENSOR_MAP_L2_PROMOTION_L2_256B, CU_TENSOR_MAP_FLOAT_OOB_FILL_NONE);
    }
    const CUtensorMap mv = make_map(enc, d_in[2], (uint64_t)NB * HKV * SK, DH, 2);
    const CUtensorMap mwo = make_map(enc, d_in[4], 4096, DM, 2);
    const CUtensorMap mw1 = make_map(enc, d_in[6], DM, DFF, 7);
    const CUtensorMap mw2 = make_map(enc, d_in[7], DFF, DM, 8);
    fused_decode_kernel<<<NCTA, NTHREADS, SMEM_BYTES, cudaStreamPerThread>>>(p, mwq, mv, mwo, mw1, mw2);
}
```

```cpp
#include <cuda_runtime.h>
#include <cuda_bf16.h>
#include <cuda.h>
#include <stdint.h>

namespace {

constexpr int NB = 4, DM = 512, HKV = 8, SK = 16384, DH = 128, WIN = 4096, DFF = 1792;
constexpr int NATT = 128, NFFN = 4, NCTA = NATT + NFFN;
constexpr int TILE_B = 8192;
constexpr int NKT = 32, NVT = 32, N2T = 2, NWT = 4, NT = NKT + NVT + N2T;
constexpr int NSLOT = 23;
constexpr int NTHREADS = 448;

constexpr int WINDOW = 4;
constexpr int TAU = 334, TOFF = 460, WTAU = 325, W2GAP = WTAU * 3 / 4, WMIN = 3, WMAX = 8;
constexpr int FOFF = 1650, FTAU = 850;
constexpr int PREW_AT = 12;
constexpr int KD_AT = 18;
constexpr int NPROBE = 40, PROBE_FAST = 410;

constexpr int FSLOT_B = 7 * 4096, FNSLOT = 6, FN1 = 16;

constexpr int SM_W = NSLOT * TILE_B;
constexpr int SM_P = SM_W + 32768;
constexpr int SM_XN = SM_P;
constexpr int SM_RED = SM_P + 4096;
constexpr int SM_O = SM_P + 8192;
constexpr int SM_Q = SM_O;
constexpr int SM_H = SM_O + 1024;
constexpr int SM_MISC = SM_H + 512;
constexpr int SM_BAR = SM_MISC + 512;
constexpr int SMEM_BYTES = SM_BAR + 8 * (NT + 2 * NWT + NSLOT + 4);
static_assert(SM_P >= FNSLOT * FSLOT_B, "ring too small for FFN");
static_assert(SMEM_BYTES <= 232448, "shared memory");

struct Scratch {
    uint32_t x[32 * 16384];
    uint32_t q[NB * 4096];
    uint32_t h[56 * 128];
    uint32_t ml[NATT * 4 * 2];
    uint32_t epoch[NCTA + 28];
};
__device__ __align__(1024) unsigned char g_scratch[sizeof(Scratch) + 65536];
__device__ __forceinline__ int xslot(int region, int s) { return region * 16384 + (2 * s + (s & 1)) * 1024; }
__device__ __forceinline__ uint32_t* other(uint32_t* p) { return (uint32_t*)((uintptr_t)p ^ 4096); }

__device__ __forceinline__ uint32_t smem_u32(const void* p) { return (uint32_t)__cvta_generic_to_shared(p); }
__device__ __forceinline__ void mbar_init(uint32_t bar, uint32_t cnt) {
    asm volatile("mbarrier.init.shared::cta.b64 [%0], %1;" :: "r"(bar), "r"(cnt) : "memory");
}
__device__ __forceinline__ void mbar_expect_tx(uint32_t bar, uint32_t bytes) {
    asm volatile("mbarrier.arrive.expect_tx.shared::cta.b64 _, [%0], %1;" :: "r"(bar), "r"(bytes) : "memory");
}
__device__ __forceinline__ void mbar_arrive(uint32_t bar, uint32_t cnt) {
    asm volatile("mbarrier.arrive.shared::cta.b64 _, [%0], %1;" :: "r"(bar), "r"(cnt) : "memory");
}
__device__ __forceinline__ bool mbar_try(uint32_t bar, uint32_t parity) {
    uint32_t ok;
    asm volatile("{\n.reg .pred p;\nmbarrier.try_wait.parity.shared::cta.b64 p, [%1], %2;\nselp.u32 %0, 1, 0, p;\n}"
                 : "=r"(ok) : "r"(bar), "r"(parity) : "memory");
    return ok != 0;
}
constexpr uint32_t SPIN_LIMIT = 1u << 22;
__device__ __forceinline__ void mbar_wait(uint32_t bar, uint32_t parity) {
    uint32_t n = 0;
    while (!mbar_try(bar, parity)) {
        if (++n > SPIN_LIMIT) __trap();
    }
}
__device__ __forceinline__ bool mbar_test(uint32_t bar, uint32_t parity) {
    uint32_t ok;
    asm volatile("{\n.reg .pred p;\nmbarrier.test_wait.parity.shared::cta.b64 p, [%1], %2;\nselp.u32 %0, 1, 0, p;\n}"
                 : "=r"(ok) : "r"(bar), "r"(parity) : "memory");
    return ok != 0;
}
__device__ __forceinline__ uint32_t now_ns() { uint32_t t; asm volatile("mov.u32 %0, %%globaltimer_lo;" : "=r"(t)); return t; }
__device__ __forceinline__ bool elect_one() {
    uint32_t pred;
    asm volatile("{\n.reg .pred p;\nelect.sync _|p, 0xffffffff;\nselp.u32 %0, 1, 0, p;\n}" : "=r"(pred));
    return pred != 0;
}
__device__ __forceinline__ uint64_t policy_stream() { return 0x12F0000000000000ull; }
__device__ __forceinline__ float ex2(float x) { float y; asm("ex2.approx.ftz.f32 %0, %1;" : "=f"(y) : "f"(x)); return y; }
__device__ __forceinline__ float rcp_fast(float x) { float y; asm("rcp.approx.ftz.f32 %0, %1;" : "=f"(y) : "f"(x)); return y; }
#define PIN(x) asm volatile("" : "+r"(x))
#define PINL(x) asm volatile("" : "+l"(x))
__device__ __forceinline__ float sqrt_fast(float x) { float y; asm("sqrt.approx.f32 %0, %1;" : "=f"(y) : "f"(x)); return y; }
__device__ __forceinline__ void bulk_g2s(uint32_t dst, const void* src, uint32_t bytes, uint32_t bar, uint64_t pol) {
    asm volatile("cp.async.bulk.shared::cluster.global.mbarrier::complete_tx::bytes.L2::cache_hint [%0], [%1], %2, [%3], %4;"
                 :: "r"(dst), "l"(src), "r"(bytes), "r"(bar), "l"(pol) : "memory");
}
__device__ __forceinline__ void tma_3d(uint32_t dst, const CUtensorMap* map, int c0, int c1, int c2, uint32_t bar, uint64_t pol) {
    asm volatile("cp.async.bulk.tensor.3d.shared::cluster.global.mbarrier::complete_tx::bytes.L2::cache_hint [%0], [%1, {%3, %4, %5}], [%2], %6;"
                 :: "r"(dst), "l"(map), "r"(bar), "r"(c0), "r"(c1), "r"(c2), "l"(pol) : "memory");
}
__device__ __forceinline__ void tma_2d(uint32_t dst, const CUtensorMap* map, int c0, int c1, uint32_t bar, uint64_t pol) {
    asm volatile("cp.async.bulk.tensor.2d.shared::cluster.global.mbarrier::complete_tx::bytes.L2::cache_hint [%0], [%1, {%3, %4}], [%2], %5;"
                 :: "r"(dst), "l"(map), "r"(bar), "r"(c0), "r"(c1), "l"(pol) : "memory");
}
__device__ __forceinline__ void prefetch_map(const CUtensorMap* map) {
    asm volatile("prefetch.tensormap [%0];" :: "l"(map) : "memory");
}
__device__ __forceinline__ void bar_sync(int id, int n) { asm volatile("bar.sync %0, %1;" :: "r"(id), "r"(n) : "memory"); }
__device__ __forceinline__ void bar_arrive(int id, int n) { asm volatile("bar.arrive %0, %1;" :: "r"(id), "r"(n) : "memory"); }

__device__ __forceinline__ uint4 lds128(uint32_t a) {
    uint4 v; asm volatile("ld.shared.v4.u32 {%0,%1,%2,%3}, [%4];" : "=r"(v.x), "=r"(v.y), "=r"(v.z), "=r"(v.w) : "r"(a) : "memory"); return v;
}
__device__ __forceinline__ float4 lds128f(uint32_t a) {
    float4 v; asm volatile("ld.shared.v4.f32 {%0,%1,%2,%3}, [%4];" : "=f"(v.x), "=f"(v.y), "=f"(v.z), "=f"(v.w) : "r"(a) : "memory"); return v;
}
__device__ __forceinline__ uint32_t lds32(uint32_t a) {
    uint32_t v; asm volatile("ld.shared.u32 %0, [%1];" : "=r"(v) : "r"(a) : "memory"); return v;
}
__device__ __forceinline__ void sts32(uint32_t a, uint32_t v) { asm volatile("st.shared.u32 [%0], %1;" :: "r"(a), "r"(v) : "memory"); }
__device__ __forceinline__ void sts16(uint32_t a, uint16_t v) { asm volatile("st.shared.u16 [%0], %1;" :: "r"(a), "h"(v) : "memory"); }
__device__ __forceinline__ float2 lds64f(uint32_t a) {
    float2 v; asm volatile("ld.shared.v2.f32 {%0,%1}, [%2];" : "=f"(v.x), "=f"(v.y) : "r"(a) : "memory"); return v;
}
__device__ __forceinline__ void sts128f(uint32_t a, float x, float y, float z, float w) {
    asm volatile("st.shared.v4.f32 [%0], {%1,%2,%3,%4};" :: "r"(a), "f"(x), "f"(y), "f"(z), "f"(w) : "memory");
}
__device__ __forceinline__ void sts128(uint32_t a, uint4 v) {
    asm volatile("st.shared.v4.u32 [%0], {%1,%2,%3,%4};" :: "r"(a), "r"(v.x), "r"(v.y), "r"(v.z), "r"(v.w) : "memory");
}
__device__ __forceinline__ uint4 ldsm_t(uint32_t a) {
    uint4 v;
    asm volatile("ldmatrix.sync.aligned.m8n8.x4.trans.shared.b16 {%0,%1,%2,%3}, [%4];"
                 : "=r"(v.x), "=r"(v.y), "=r"(v.z), "=r"(v.w) : "r"(a) : "memory");
    return v;
}
__device__ __forceinline__ void ldsm_t_if(uint4& v, uint32_t a, bool pred) {
    asm volatile("{\n.reg .pred p;\nsetp.ne.u32 p, %5, 0;\n@p ldmatrix.sync.aligned.m8n8.x4.trans.shared.b16 {%0,%1,%2,%3}, [%4];\n}"
                 : "+r"(v.x), "+r"(v.y), "+r"(v.z), "+r"(v.w) : "r"(a), "r"((uint32_t)pred) : "memory");
}
__device__ __forceinline__ void mma(float (&c)[4], uint32_t a0, uint32_t a1, uint32_t a2, uint32_t a3, uint32_t b0, uint32_t b1) {
    asm volatile("mma.sync.aligned.m16n8k16.row.col.f32.bf16.bf16.f32 {%0,%1,%2,%3}, {%4,%5,%6,%7}, {%8,%9}, {%0,%1,%2,%3};"
                 : "+f"(c[0]), "+f"(c[1]), "+f"(c[2]), "+f"(c[3])
                 : "r"(a0), "r"(a1), "r"(a2), "r"(a3), "r"(b0), "r"(b1));
}
__device__ __forceinline__ uint32_t pack_bf16(float lo, float hi) {
    uint32_t r; asm("cvt.rn.bf16x2.f32 %0, %1, %2;" : "=r"(r) : "f"(hi), "f"(lo)); return r;
}
__device__ __forceinline__ float rbf(float x) { return __uint_as_float(pack_bf16(0.f, x) & 0xffff0000u); }
__device__ __forceinline__ float bf_lo(uint32_t v) { return __uint_as_float(v << 16); }
__device__ __forceinline__ float bf_hi(uint32_t v) { return __uint_as_float(v & 0xffff0000u); }
__device__ __forceinline__ uint16_t bf_bits(float x) { return (uint16_t)pack_bf16(x, 0.f); }

__device__ __forceinline__ uint32_t tg(float v, uint32_t tag) {
    uint32_t r; asm("lop3.b32 %0, %1, 0xfffffff0, %2, 0xea;" : "=r"(r) : "r"(__float_as_uint(v)), "r"(tag)); return r;
}
__device__ __forceinline__ float untg(uint32_t w) { return __uint_as_float(w & ~15u); }
__device__ __forceinline__ bool bad2(uint2 v, uint32_t tag) { return (((v.x ^ tag) | (v.y ^ tag)) & 15u) != 0; }
__device__ __forceinline__ bool bad4(uint4 v, uint32_t tag) { return (((v.x ^ tag) | (v.y ^ tag) | (v.z ^ tag) | (v.w ^ tag)) & 15u) != 0; }
__device__ __forceinline__ uint32_t dif2(uint32_t a, uint32_t b, uint32_t tag) {
    uint32_t r; asm("lop3.b32 %0, %1, %2, %3, 0x7e;" : "=r"(r) : "r"(a), "r"(b), "r"(tag)); return r;
}
__device__ __forceinline__ uint32_t or3(uint32_t a, uint32_t b, uint32_t c) {
    uint32_t r; asm("lop3.b32 %0, %1, %2, %3, 0xfe;" : "=r"(r) : "r"(a), "r"(b), "r"(c)); return r;
}
__device__ __forceinline__ uint32_t clk32() { uint32_t c; asm volatile("mov.u32 %0, %%clock;" : "=r"(c) :: "memory"); return c; }
__device__ __forceinline__ float asf(uint32_t w) { return __uint_as_float(w); }
__device__ __forceinline__ void ll_st2(uint32_t* p, uint32_t a, uint32_t b) {
    asm volatile("st.relaxed.gpu.global.v2.b32 [%0], {%1, %2};" :: "l"(p), "r"(a), "r"(b) : "memory");
}
__device__ __forceinline__ uint2 ll_ld2(const uint32_t* p) {
    uint2 v; asm volatile("ld.relaxed.gpu.global.v2.b32 {%0, %1}, [%2];" : "=r"(v.x), "=r"(v.y) : "l"(p) : "memory"); return v;
}
__device__ __forceinline__ uint4 ll_ld4(const uint32_t* p) {
    uint4 v; asm volatile("ld.relaxed.gpu.global.v4.b32 {%0, %1, %2, %3}, [%4];" : "=r"(v.x), "=r"(v.y), "=r"(v.z), "=r"(v.w) : "l"(p) : "memory"); return v;
}
__device__ __forceinline__ void ll_ld4_if(uint4& v, const uint32_t* p, uint32_t pred) {
    asm volatile("{\n.reg .pred q;\nsetp.ne.u32 q, %5, 0;\n@q ld.relaxed.gpu.global.v4.b32 {%0, %1, %2, %3}, [%4];\n}"
                 : "+r"(v.x), "+r"(v.y), "+r"(v.z), "+r"(v.w) : "l"(p), "r"(pred) : "memory");
}
__device__ __forceinline__ void ll_ld2_if(uint2& v, const uint32_t* p, uint32_t pred) {
    asm volatile("{\n.reg .pred q;\nsetp.ne.u32 q, %3, 0;\n@q ld.relaxed.gpu.global.v2.b32 {%0, %1}, [%2];\n}"
                 : "+r"(v.x), "+r"(v.y) : "l"(p), "r"(pred) : "memory");
}
__device__ __forceinline__ void prefetch_l2(const void* p) {
    asm volatile("cp.async.bulk.prefetch.L2.global [%0], 128;" :: "l"(p) : "memory");
}
__device__ __forceinline__ uint4 ldg128_nc(const void* p) {
    uint4 v; asm volatile("ld.global.nc.v4.u32 {%0,%1,%2,%3}, [%4];" : "=r"(v.x), "=r"(v.y), "=r"(v.z), "=r"(v.w) : "l"(p)); return v;
}
__device__ __forceinline__ float warp_sum(float v) {
#pragma unroll
    for (int o = 16; o; o >>= 1) v += __shfl_xor_sync(0xffffffffu, v, o);
    return v;
}

__device__ __forceinline__ void layernorm_row(const uint4 xa, const uint4 xb, int b, int lane, uint32_t sxn) {
    float v[16];
    v[0] = bf_lo(xa.x); v[1] = bf_hi(xa.x); v[2] = bf_lo(xa.y); v[3] = bf_hi(xa.y);
    v[4] = bf_lo(xa.z); v[5] = bf_hi(xa.z); v[6] = bf_lo(xa.w); v[7] = bf_hi(xa.w);
    v[8] = bf_lo(xb.x); v[9] = bf_hi(xb.x); v[10] = bf_lo(xb.y); v[11] = bf_hi(xb.y);
    v[12] = bf_lo(xb.z); v[13] = bf_hi(xb.z); v[14] = bf_lo(xb.w); v[15] = bf_hi(xb.w);
    float s = 0.f;
#pragma unroll
    for (int i = 0; i < 16; i++) s += v[i];
    const float mean = warp_sum(s) * (1.0f / DM);
    float q = 0.f;
#pragma unroll
    for (int i = 0; i < 16; i++) { const float d = v[i] - mean; q += d * d; }
    const float var = warp_sum(q) * (1.0f / DM);
    const float mb = rbf(mean);
    const float rs = __fdividef(1.0f, rbf(sqrt_fast(rbf(rbf(var) + 1e-5f))));
#pragma unroll
    for (int hlf = 0; hlf < 2; hlf++) {
        const uint32_t base = sxn + (hlf * 8 + (lane >> 2)) * 256 + b * 64 + (lane & 3) * 4;
#pragma unroll
        for (int i = 0; i < 4; i++) {
            const float lo = rbf(v[hlf * 8 + 2 * i] - mb) * rs;
            const float hi = rbf(v[hlf * 8 + 2 * i + 1] - mb) * rs;
            sts32(base + i * 16, pack_bf16(lo, hi));
        }
    }
}

struct Params {
    const __nv_bfloat16* x;
    const __nv_bfloat16* k;
    const __nv_bfloat16* v;
    const __nv_bfloat16* wo;
    __nv_bfloat16* out;
    Scratch* sc;
};

__global__ void __launch_bounds__(NTHREADS, 1)
fused_decode_kernel(const Params p, const __grid_constant__ CUtensorMap map_wq,
                    const __grid_constant__ CUtensorMap map_v, const __grid_constant__ CUtensorMap map_wo,
                    const __grid_constant__ CUtensorMap map_w1, const __grid_constant__ CUtensorMap map_w2) {
    extern __shared__ uint8_t smem_raw[];
    constexpr uint32_t sb = 1024;
    const int tid = threadIdx.x, lane = tid & 31;
    const int cta = blockIdx.x;
    const bool att = cta < NATT;
    const uint32_t s_full = sb + SM_BAR, s_wo = s_full + 8 * NT, s_wq = s_wo + 8 * NWT, s_empty = s_wq + 8 * NWT;
    const uint32_t s_wrdy = s_empty + 8 * NSLOT, s_kd = s_wrdy + 8, s_vd = s_wrdy + 16, s_fd = s_wrdy + 24;
    const int kvh = cta >> 4, r = cta & 15, b = r >> 2, j = r & 3;
    const size_t kvoff = ((size_t)(b * HKV + kvh) * SK + (SK - WIN)) * DH * 2;
    const int grp = b * HKV + kvh;
    auto tpos = [&](int t) { return t < 4 ? 4 * j + t : (((t >> 2) << 4) | ((j >> 1) << 3) | ((t & 1) << 2) | ((j & 1) << 1) | ((t >> 1) & 1)); };
    const char* kbase = (const char*)p.k + kvoff;

    if (tid == 256) {
        mbar_init(s_full, 1);
        if (att) {
            bulk_g2s(sb, kbase + j * 4 * TILE_B, 4 * TILE_B, s_full, policy_stream());
            mbar_expect_tx(s_full, 4 * TILE_B);
        }
    }
    __syncwarp();
    const int warp = __shfl_sync(0xffffffffu, tid >> 5, 0);

    const uint32_t s_tag = sb + SM_MISC + 384;
    const int g = lane >> 2, t = lane & 3;
    const int bsel = ((t & 1) << 1) | (t >> 1);
    const bool lo = t < 2;
    const int lrow = (lane & 7) + ((lane >> 4) << 3);
    const int lchk = (lane >> 3) & 1;
    const uint32_t boff = (g & 3) * 64 + t * 16;
    const float L2E = 1.4426950408889634f;

    if (warp < 8) {
        uint32_t* const q_dst = p.sc->q + (tid >> 4) * 4096 + cta * 32 + (tid & 15) * 2;
        uint4 xa = make_uint4(0u, 0u, 0u, 0u), xb = xa;
        if (warp < NB) {
            xa = ldg128_nc(p.x + warp * DM + lane * 8);
            xb = ldg128_nc(p.x + warp * DM + 256 + lane * 8);
        }
        if (tid == 255) {
            uint32_t e = *(volatile unsigned int*)&p.sc->epoch[cta];
            e = e >= 15u ? 1u : e + 1u;
            *(volatile unsigned int*)&p.sc->epoch[cta] = e;
            sts32(s_tag, e);
        }
        if (att) {
            if (tid < 64) ll_st2(q_dst, 0u, 0u);
            if (tid < 16 && t == 0) ll_st2(p.sc->ml + (cta * 4 + g) * 2, 0u, 0u);
        }
        if (warp < NB) layernorm_row(xa, xb, warp, lane, sb + SM_XN);
        __syncwarp();
        bar_sync(1, NTHREADS);
        const uint32_t tag = lds32(s_tag);
        if (att) {
            {
                float c0[4] = {0.f, 0.f, 0.f, 0.f}, c1[4] = {0.f, 0.f, 0.f, 0.f};
                const uint32_t xs = sb + SM_XN + warp * 512 + boff;
                const uint4 b0 = lds128(xs), b1 = lds128(xs + 256);
                const uint32_t bb[8] = {b0.x, b0.y, b0.z, b0.w, b1.x, b1.y, b1.z, b1.w};
                const uint32_t wa = sb + SM_W + (warp * 64 + lrow) * 64;
                const uint32_t sw = (lrow >> 1) & 3;
                mbar_wait(s_wq + 8 * (warp >> 2), 0);
#pragma unroll
                for (int ks = 0; ks < 4; ks++) {
                    const uint4 v0 = ldsm_t(wa + ks * 1024 + ((lchk ^ sw) << 4)), v1 = ldsm_t(wa + ks * 1024 + (((2 + lchk) ^ sw) << 4));
                    mma(c0, v0.x, v0.y, v0.z, v0.w, bb[2 * ks], bb[2 * ks + 1]);
                    mma(c1, v1.x, v1.y, v1.z, v1.w, bb[2 * ks], bb[2 * ks + 1]);
                }
                sts128f(sb + SM_RED + warp * 512 + bsel * 128 + g * 16,
                        lo ? c0[0] : c0[1], lo ? c0[2] : c0[3], lo ? c1[0] : c1[1], lo ? c1[2] : c1[3]);
                bar_sync(2, 256);
                if (tid < 64) {
                    float s0 = 0.f, s1 = 0.f;
#pragma unroll
                    for (int w = 0; w < 8; w++) { const float2 v = lds64f(sb + SM_RED + w * 512 + tid * 8); s0 += v.x; s1 += v.y; }
                    ll_st2(q_dst, tg(rbf(s0), tag), tg(rbf(s1), tag));
                }
                const uint32_t* src = p.sc->q + b * 4096 + kvh * 512 + tid * 2;
                uint2 v = ll_ld2(src);
                uint32_t n = 0;
                while (bad2(v, tag)) {
                    __nanosleep(500);
                    if (++n > SPIN_LIMIT) __trap();
                    v = ll_ld2(src);
                }
                const uint32_t qa = sb + SM_Q + ((tid >> 4) * 32 + (tid & 1) * 16 + ((tid & 15) >> 1)) * 2;
                sts16(qa, (uint16_t)(v.x >> 16));
                sts16(qa + 16, (uint16_t)(v.y >> 16));
                __syncwarp();
            }
            const uint32_t aoff = (warp >> 2) * 4096 + lrow * 128 + ((((warp & 3) * 2 + lchk) ^ (lrow & 7)) << 4);
            uint32_t* const o_dst = p.sc->x + xslot(kvh * 4 + bsel, j >> 1) + ((j & 1) * NB + b) * 128 + warp * 16 + g * 2;
            uint32_t* const y_dst = p.sc->x + xslot(bsel * 8 + j * 2 + (warp >> 2), 2 + (warp & 3)) + (cta >> 2) * 16 + g * 2;
            uint32_t* const o_dst2 = other(o_dst);
            uint32_t* const y_dst2 = other(y_dst);
            const uint32_t* o_src = p.sc->x + xslot(cta >> 2, 0) + tid * 2;
            const uint32_t* o_src2 = p.sc->x + xslot(cta >> 2, 1) + tid * 2;
            uint32_t oa = sb + SM_O + ((tid & 63) >> 4) * 256 + (tid >> 6) * 64 + ((tid & 7) >> 1) * 16 + (tid & 8) + (tid & 1) * 2;
            uint32_t ob_a = sb + SM_O + boff;
            float4 wj = make_float4(0.f, 0.f, 0.f, 0.f);
            bar_sync(2, 256);
            {
                {
                    {
                        uint4 qb[4];
#pragma unroll
                        for (int c = 0; c < 4; c++) qb[c] = lds128(sb + SM_Q + (g & 3) * 256 + (4 * (c ^ (g >> 2)) + t) * 16);
                        const uint32_t koff = (2 * g) * 256 + t * 16;
                        const bool valid = (g & 1) == (t >> 1);
                        const uint32_t pa = sb + SM_P + (t & 1) * 128 + (g & 3) * 16 + (g >> 2) * 4;
                        float mA = -INFINITY, mB = -INFINITY;
#pragma unroll 1
                        for (int tt = warp; tt < NKT; tt += 8) {
                            const int slot = tt >= NSLOT ? tt - NSLOT : tt;
                            mbar_wait(s_full + (tt < 4 ? 0 : 8 * tt), 0);
                            const uint32_t ka = sb + slot * TILE_B + koff;
                            float sc[2][4] = {{0.f, 0.f, 0.f, 0.f}, {0.f, 0.f, 0.f, 0.f}};
#pragma unroll
                            for (int c = 0; c < 4; c++) {
#pragma unroll
                                for (int mt = 0; mt < 2; mt++) {
                                    const uint32_t a = ka + mt * 4096 + ((c ^ (g & 1)) << 6);
                                    const uint4 x = lds128(a), y = lds128(a + 256);
                                    mma(sc[mt], x.x, y.x, x.y, y.y, qb[c].x, qb[c].y);
                                    mma(sc[mt], x.z, y.z, x.w, y.w, qb[c].z, qb[c].w);
                                }
                            }
                            __syncwarp();
                            if (lane == 0) mbar_arrive(s_empty + 8 * slot, 8);
                            if (valid) {
#pragma unroll
                                for (int mt = 0; mt < 2; mt++) {
                                    const uint32_t ra = pack_bf16(sc[mt][0], sc[mt][2]), rb = pack_bf16(sc[mt][1], sc[mt][3]);
                                    const float SC = 0.08838834764831845f;
                                    const uint32_t sa = pack_bf16(bf_lo(ra) * SC, bf_hi(ra) * SC), sbb = pack_bf16(bf_lo(rb) * SC, bf_hi(rb) * SC);
                                    mA = fmaxf(mA, fmaxf(bf_lo(sa), bf_hi(sa)));
                                    mB = fmaxf(mB, fmaxf(bf_lo(sbb), bf_hi(sbb)));
                                    sts32(pa + tt * 256 + mt * 8, sa);
                                    sts32(pa + tt * 256 + mt * 8 + 64, sbb);
                                }
                            }
                        }
#pragma unroll
                        for (int o = 2; o <= 16; o <<= 1) {
                            mA = fmaxf(mA, __shfl_xor_sync(0xffffffffu, mA, o));
                            mB = fmaxf(mB, __shfl_xor_sync(0xffffffffu, mB, o));
                        }
                        if (lane < 2) { sts32(sb + SM_MISC + lane * 64 + warp * 4, __float_as_uint(mA)); sts32(sb + SM_MISC + lane * 64 + 32 + warp * 4, __float_as_uint(mB)); }
                    }
                    bar_sync(2, 256);
                    {
                        const float4 m0 = lds128f(sb + SM_MISC + (g & 3) * 32), m1 = lds128f(sb + SM_MISC + (g & 3) * 32 + 16);
                        const float m = fmaxf(fmaxf(fmaxf(m0.x, m0.y), fmaxf(m0.z, m0.w)), fmaxf(fmaxf(m1.x, m1.y), fmaxf(m1.z, m1.w)));
                        float l = 0.f;
#pragma unroll
                        for (int hf = 0; hf < 2; hf++) {
                            const uint32_t a = sb + SM_P + hf * 4096 + tid * 16;
                            const uint4 v = lds128(a);
                            uint32_t w[4] = {v.x, v.y, v.z, v.w};
#pragma unroll
                            for (int e = 0; e < 4; e++) {
                                const float p0 = ex2((bf_lo(w[e]) - m) * L2E), p1 = ex2((bf_hi(w[e]) - m) * L2E);
                                l += p0 + p1;
                                w[e] = pack_bf16(p0, p1);
                            }
                            sts128(a, make_uint4(w[0], w[1], w[2], w[3]));
                        }
                        l += __shfl_xor_sync(0xffffffffu, l, 1);
                        l += __shfl_xor_sync(0xffffffffu, l, 2);
                        l += __shfl_xor_sync(0xffffffffu, l, 16);
                        if (lane < 16 && t == 0) sts32(sb + SM_MISC + 128 + g * 32 + warp * 4, __float_as_uint(l));
                        bar_sync(2, 256);
                        if (tid < 16 && t == 0) {
                            const float4 l0 = lds128f(sb + SM_MISC + 128 + g * 32), l1 = lds128f(sb + SM_MISC + 128 + g * 32 + 16);
                            ll_st2(p.sc->ml + (cta * 4 + g) * 2, tg(m, tag), tg(((l0.x + l0.y) + (l0.z + l0.w)) + ((l1.x + l1.y) + (l1.z + l1.w)), tag));
                        }
                    }
                    PIN(oa); PIN(ob_a);
                    float a0[4] = {0.f, 0.f, 0.f, 0.f}, a1[4] = {0.f, 0.f, 0.f, 0.f};
                    int slot = NKT % NSLOT;
#pragma unroll 1
                    for (int i = 0; i < NVT; i++) {
                        const uint4 pb = lds128(sb + SM_P + i * 256 + boff);
                        if (i == PREW_AT + warp) {
                            ll_st2(o_dst, 0u, 0u); ll_st2(o_dst2, 0u, 0u);
                            ll_st2(y_dst, 0u, 0u); ll_st2(y_dst2, 0u, 0u);
                        }
                        if (i == KD_AT && tid == 0) mbar_arrive(s_kd, 1);
                        if (i == NVT - 2) {
                            mbar_wait(s_wrdy, 0);
                            wj = lds128f(sb + SM_MISC + 256 + (tid >> 6) * 16);
                            const uint32_t sel = lds32(s_tag + 4);
                            o_src = (const uint32_t*)((uintptr_t)o_src ^ sel);
                            o_src2 = (const uint32_t*)((uintptr_t)o_src2 ^ sel);
                        }
                        mbar_wait(s_full + 8 * (NKT + i), 0);
                        const uint32_t va = sb + slot * TILE_B + aoff;
                        const uint4 v0 = ldsm_t(va), v1 = ldsm_t(va + 2048);
                        mma(a0, v0.x, v0.y, v0.z, v0.w, pb.x, pb.y);
                        mma(a1, v1.x, v1.y, v1.z, v1.w, pb.z, pb.w);
                        if (i + NKT + NSLOT < NT) {
                            __syncwarp();
                            if (lane == 0) mbar_arrive(s_empty + 8 * slot, 1);
                        }
                        if (++slot == NSLOT) slot = 0;
                    }
                    const uint32_t o0 = tg(lo ? a0[0] + a1[0] : a0[1] + a1[1], tag), o1 = tg(lo ? a0[2] + a1[2] : a0[3] + a1[3], tag);
                    ll_st2(o_dst, o0, o1);
                    ll_st2(o_dst2, o0, o1);
                }
                uint4 wa[8];
                const uint32_t wbase = sb + SM_W + aoff;
#pragma unroll
                for (int i = 0; i < 8; i++) wa[i] = make_uint4(0u, 0u, 0u, 0u);
                uint32_t got = 0;
                {
                    uint2 v[4];
                    uint32_t n = 0;
#pragma unroll
                    for (int i = 0; i < 4; i++) v[i] = make_uint2(0u, 0u);
                    while (true) {
                        uint32_t bd[4];
#pragma unroll
                        for (int i = 0; i < 4; i++) {
                            bd[i] = dif2(v[i].x, v[i].y, tag) & 15u;
                            ll_ld2_if(v[i], (i < 2 ? o_src : o_src2) + (i & 1) * 512, bd[i]);
                        }
                        if (!__any_sync(0xffffffffu, (or3(bd[0], bd[1], bd[2]) | bd[3]) != 0)) break;
                        const uint32_t pick = __all_sync(0xffffffffu, mbar_test(s_wo + 8 * got, 0)) ? got : NWT;
#pragma unroll
                        for (int i = 0; i < NWT; i++) {
                            ldsm_t_if(wa[2 * i], wbase + i * TILE_B, pick == i);
                            ldsm_t_if(wa[2 * i + 1], wbase + i * TILE_B + 2048, pick == i);
                        }
                        got += pick != NWT;
                        if (++n > SPIN_LIMIT) __trap();
                    }
                    const float o0 = (wj.x * asf(v[0].x) + wj.y * asf(v[1].x)) + (wj.z * asf(v[2].x) + wj.w * asf(v[3].x));
                    const float o1 = (wj.x * asf(v[0].y) + wj.y * asf(v[1].y)) + (wj.z * asf(v[2].y) + wj.w * asf(v[3].y));
                    const uint32_t op = pack_bf16(o0, o1);
                    sts16(oa, (uint16_t)op);
                    sts16(oa + 4, (uint16_t)(op >> 16));
                }
                {
                    if (got != NWT) {
                        const uint32_t rdy = __ballot_sync(0xffffffffu, mbar_test(s_wo + 8 * (lane & 3), 0)) & 15u;
                        const uint32_t upto = __ffs(~rdy) - 1;
                        __syncwarp();
#pragma unroll
                        for (int i = 0; i < NWT; i++) {
                            ldsm_t_if(wa[2 * i], wbase + i * TILE_B, i >= got && i < upto);
                            ldsm_t_if(wa[2 * i + 1], wbase + i * TILE_B + 2048, i >= got && i < upto);
                        }
                        got = max(got, upto);
                    }
                    bar_sync(2, 256);
                    uint4 ob[4];
#pragma unroll
                    for (int i = 0; i < NWT; i++) ob[i] = lds128(ob_a + i * 256);
                    if (tid == 0) mbar_arrive(s_vd, 1);
                    float c[4][4];
#pragma unroll
                    for (int i = 0; i < 4; i++) c[i][0] = c[i][1] = c[i][2] = c[i][3] = 0.f;
                    if (got == NWT) {
#pragma unroll
                        for (int i = 0; i < NWT; i++) {
                            mma(c[(2 * i) & 3], wa[2 * i].x, wa[2 * i].y, wa[2 * i].z, wa[2 * i].w, ob[i].x, ob[i].y);
                            mma(c[(2 * i + 1) & 3], wa[2 * i + 1].x, wa[2 * i + 1].y, wa[2 * i + 1].z, wa[2 * i + 1].w, ob[i].z, ob[i].w);
                        }
                    } else {
#pragma unroll
                        for (int i = 0; i < NWT; i++) {
                            if (got <= i) {
                                mbar_wait(s_wo + 8 * i, 0);
                                const uint32_t va = sb + SM_W + i * TILE_B + aoff;
                                wa[2 * i] = ldsm_t(va); wa[2 * i + 1] = ldsm_t(va + 2048);
                            }
                            mma(c[(2 * i) & 3], wa[2 * i].x, wa[2 * i].y, wa[2 * i].z, wa[2 * i].w, ob[i].x, ob[i].y);
                            mma(c[(2 * i + 1) & 3], wa[2 * i + 1].x, wa[2 * i + 1].y, wa[2 * i + 1].z, wa[2 * i + 1].w, ob[i].z, ob[i].w);
                        }
                    }
                    const float r0 = lo ? (c[0][0] + c[1][0]) + (c[2][0] + c[3][0]) : (c[0][1] + c[1][1]) + (c[2][1] + c[3][1]);
                    const float r1 = lo ? (c[0][2] + c[1][2]) + (c[2][2] + c[3][2]) : (c[0][3] + c[1][3]) + (c[2][3] + c[3][3]);
                    const uint32_t y0 = tg(r0, tag), y1 = tg(r1, tag);
                    ll_st2(y_dst, y0, y1);
                    ll_st2(y_dst2, y0, y1);
                }
            }
        } else {
            const int f = cta - NATT;
            const uint32_t arow = warp * 4096 + lrow * 128;
            float c[4][4];
            int slot = 0, ph = 0;
#pragma unroll
            for (int i = 0; i < 4; i++) c[i][0] = c[i][1] = c[i][2] = c[i][3] = 0.f;
            if (warp < 7) {
#pragma unroll 1
                for (int tt = 0; tt < FN1; tt++) {
                    const uint4 bb = lds128(sb + SM_XN + tt * 256 + boff);
                    mbar_wait(s_full + 8 * slot, ph);
                    const uint32_t va = sb + slot * FSLOT_B + arow;
#pragma unroll
                    for (int i = 0; i < 4; i++) {
                        const uint32_t sw = ((2 * i + lchk) ^ (lrow & 7)) << 4;
                        const uint4 v0 = ldsm_t(va + sw), v1 = ldsm_t(va + sw + 2048);
                        mma(c[i], v0.x, v0.y, v0.z, v0.w, bb.x, bb.y);
                        mma(c[i], v1.x, v1.y, v1.z, v1.w, bb.z, bb.w);
                    }
                    __syncwarp();
                    if (lane == 0) mbar_arrive(s_empty + 8 * slot, 1);
                    if (++slot == FNSLOT) { slot = 0; ph ^= 1; }
                }
#pragma unroll
                for (int i = 0; i < 4; i++) {
                    const float h0 = fmaxf(lo ? c[i][0] : c[i][1], 0.f), h1 = fmaxf(lo ? c[i][2] : c[i][3], 0.f);
                    const uint32_t ha = sb + SM_RED + (2 * warp + (i >> 1)) * 256 + bsel * 64 + (g >> 1) * 16 + (i & 1) * 8 + (g & 1) * 2;
                    sts16(ha, bf_bits(h0));
                    sts16(ha + 4, bf_bits(h1));
                }
                __syncwarp();
#pragma unroll
                for (int i = 0; i < 4; i++) {
                    const uint32_t w = lds32(sb + SM_RED + warp * 512 + i * 128 + lane * 4);
                    ll_st2(p.sc->h + (f * 14 + 2 * warp) * 128 + i * 64 + lane * 2, (w << 16) | tag, (w & 0xffff0000u) | tag);
                }
            }
        }
    } else if (warp >= 10) {
        if (!att) { bar_arrive(1, NTHREADS); return; }
        bar_sync(1, NTHREADS);
        const uint32_t tag = lds32(s_tag);
        uint32_t* fd[2];
        uint32_t ao[2];
#pragma unroll
        for (int m = 0; m < 2; m++) {
            const int w = (warp - 10) * 2 + m;
            fd[m] = p.sc->x + xslot(bsel * 8 + j * 2 + (w >> 2), 2 + (w & 3)) + 512 + (cta >> 2) * 16 + g * 2;
            ao[m] = (w >> 2) * 4096 + lrow * 128 + ((((w & 3) * 2 + lchk) ^ (lrow & 7)) << 4);
        }
        mbar_wait(s_wrdy, 0);
#pragma unroll
        for (int m = 0; m < 2; m++) { ll_st2(fd[m], 0u, 0u); ll_st2(other(fd[m]), 0u, 0u); }
        float c[2][2][4];
#pragma unroll
        for (int e = 0; e < 4; e++) c[0][0][e] = c[0][1][e] = c[1][0][e] = c[1][1][e] = 0.f;
#pragma unroll
        for (int i = 0; i < N2T; i++) {
            if (i == 0 || cta < 96) {
                const uint4 hb = lds128(sb + SM_H + i * 256 + boff);
                mbar_wait(s_full + 8 * (NKT + NVT + i), 0);
#pragma unroll
                for (int m = 0; m < 2; m++) {
                    const uint32_t va = sb + ((NKT + NVT + i) % NSLOT) * TILE_B + ao[m];
                    const uint4 v0 = ldsm_t(va), v1 = ldsm_t(va + 2048);
                    mma(c[m][0], v0.x, v0.y, v0.z, v0.w, hb.x, hb.y);
                    mma(c[m][1], v1.x, v1.y, v1.z, v1.w, hb.z, hb.w);
                }
            }
        }
#pragma unroll
        for (int m = 0; m < 2; m++) {
            const uint32_t f0 = tg(lo ? c[m][0][0] + c[m][1][0] : c[m][0][1] + c[m][1][1], tag);
            const uint32_t f1 = tg(lo ? c[m][0][2] + c[m][1][2] : c[m][0][3] + c[m][1][3], tag);
            ll_st2(fd[m], f0, f1);
            ll_st2(other(fd[m]), f0, f1);
        }
        if (tid == 320) mbar_arrive(s_fd, 1);
    } else if (warp == 8) {
        const uint32_t t_start = now_ns();
        const bool leader = elect_one();
        const uint64_t pol = policy_stream();
        if (att) {
            if (leader) {
#pragma unroll
                for (int i = WINDOW; i < NT + NWT; i++) mbar_init(s_full + 8 * i, 1);
                prefetch_map(&map_v); prefetch_map(&map_w2); prefetch_map(&map_wo);
            }
            __syncwarp();
            bar_sync(3, 64);
            bar_arrive(1, NTHREADS);
            for (int i = WINDOW + lane; i < NT + NWT; i += 32) mbar_expect_tx(s_full + 8 * i, i == NT - 1 && cta >= 96 ? 0 : TILE_B);
            __syncwarp();
            if (leader) {
                uint32_t due = t_start + TOFF + WINDOW * TAU;
                uint32_t bar = s_full + 8 * WINDOW, dst = sb + WINDOW * TILE_B, ebar = s_empty + 8 * WINDOW, epar = 1;
                auto pace = [&](bool ring, uint32_t lowbar) {
                    if (ring) mbar_wait(ebar, epar);
                    for (uint32_t n = 0; (int)(now_ns() - due) < 0 && !mbar_test(lowbar, 0) && n < SPIN_LIMIT; n++) {}
                };
                auto advance = [&](uint32_t step, bool check) {
                    due += step;
                    if (check && !mbar_test(bar - 8 * 5, 0)) {
                        due += 20;
                        if (!mbar_test(bar - 8 * (WMAX - 1), 0)) { due += 100; mbar_wait(bar - 8 * (WMAX - 1), 0); }
                    }
                    bar += 8; dst += TILE_B; ebar += 8;
                    if (ebar == s_empty + 8 * NSLOT) { dst = sb; ebar = s_empty; epar ^= 1; }
                };
#pragma unroll 1
                for (int t4 = WINDOW; t4 < NKT; t4 += 4) {
#pragma unroll
                    for (int e = 0; e < 4; e++) {
                        const char* src = kbase + (t4 * 4 + tpos(4 + e) - 16) * TILE_B;
                        pace(true, t4 == WINDOW && e < WMIN ? s_full : bar - 8 * WMIN);
                        bulk_g2s(dst, src, TILE_B, bar, pol);
                        advance(TAU, t4 >= 12);
                    }
                    if (t4 == 12) prefetch_l2((const char*)p.v + kvoff + tpos(0) * TILE_B);
                }
                const int vrow0 = grp * SK + (SK - WIN);
#pragma unroll 1
                for (int t4 = 0; t4 < NVT; t4 += 4) {
#pragma unroll
                    for (int e = 0; e < 4; e++) {
                        const int row = vrow0 + (t4 == 0 ? tpos(e) : t4 * 4 + tpos(4 + e) - 16) * 32;
                        pace(true, bar - 8 * WMIN);
                        tma_3d(dst, &map_v, 0, row, 0, bar, pol);
                        advance(t4 + e == NVT - 1 ? WTAU : TAU, true);
                    }
                    if (t4 == 12) prefetch_l2(p.wo + (size_t)(cta >> 2) * 128 * DM + j * 128);
                }
#pragma unroll
                for (int i = 0; i < N2T; i++) {
                    if (i == 0 || cta < 96) {
                        pace(true, bar - 8 * WMIN);
                        tma_3d(dst, &map_w2, 0, ((cta >> 2) + i * 32) * 32, j * 2, bar, pol);
                    }
                    advance(i == 0 ? WTAU : W2GAP, true);
                }
#pragma unroll 1
                for (int i = 0; i < NWT; i++) {
                    pace(false, bar - 8 * WMIN);
                    tma_3d(sb + SM_W + i * TILE_B, &map_wo, 0, (cta >> 2) * 128 + i * 32, j * 2, bar, pol);
                    advance(WTAU, true);
                }
            }
        } else {
            const int f = cta - NATT;
            if (leader) {
#pragma unroll
                for (int i = 0; i < FNSLOT; i++) { if (i) mbar_init(s_full + 8 * i, 1); mbar_init(s_empty + 8 * i, 7); }
            }
            __syncwarp();
            bar_arrive(1, NTHREADS);
            if (leader) {
                int slot = 0, ph = 0;
#pragma unroll 1
                for (int tt = 0; tt < FN1; tt++) {
                    if (tt >= FNSLOT) mbar_wait(s_empty + 8 * slot, ph ^ 1);
#pragma unroll 1
                    for (uint32_t n = 0; (int)(now_ns() - (t_start + FOFF + tt * FTAU)) < 0 && n < 4096; n++) __nanosleep(50);
                    mbar_expect_tx(s_full + 8 * slot, FSLOT_B);
                    tma_3d(sb + slot * FSLOT_B, &map_w1, 0, tt * 32, f * 7, s_full + 8 * slot, pol);
                    if (++slot == FNSLOT) { slot = 0; ph ^= 1; }
                }
            }
        }
    } else {
        if (att) {
            if (elect_one()) {
                const uint64_t pol = policy_stream();
                mbar_init(s_wq, 1);
                mbar_init(s_wq + 8, 1);
                tma_2d(sb + SM_W, &map_wq, cta * 32, 0, s_wq, pol);
                tma_2d(sb + SM_W + 16384, &map_wq, cta * 32, 256, s_wq + 8, pol);
                mbar_expect_tx(s_wq, 16384);
                mbar_expect_tx(s_wq + 8, 16384);
#pragma unroll
                for (int i = 0; i < NSLOT; i++) mbar_init(s_empty + 8 * i, 8);
#pragma unroll
                for (int i = 0; i < 4; i++) mbar_init(s_wrdy + 8 * i, 1);
            }
            __syncwarp();
            bar_arrive(3, 64);
        }
        if (smem_u32(smem_raw) != sb) __trap();
        if (!att) { bar_arrive(1, NTHREADS); return; }
        const int rb = cta >> 5, cg = cta & 31;
        const int ocol = 2 * (lane & 3) + ((lane >> 4) & 1) + (lane & 8);
        const float xres = __bfloat162float(p.x[rb * DM + cg * 16 + ocol]);
        bar_sync(1, NTHREADS);
        uint32_t sel;
        {
            uint32_t* pr = p.sc->x + xslot(cta >> 2, 6) + j * 256;
            ll_st2(pr + (lane >> 2) * 32 + (lane & 3) * 2, 0u, 0u);
            ll_st2(pr + 1024 + (lane >> 2) * 32 + (lane & 3) * 2, 0u, 0u);
            __syncwarp();
            uint32_t best[2] = {~0u, ~0u};
            auto ping = [&](uint32_t* a) {
                uint32_t v = 0;
                asm volatile("{\n.reg .pred q;\nsetp.eq.u32 q, %2, 0;\n@q atom.relaxed.gpu.global.exch.b32 %0, [%1], 0;\n}"
                             : "+r"(v) : "l"(a), "r"(lane) : "memory");
                return __any_sync(0xffffffffu, v != 0);
            };
#pragma unroll 1
            for (int i = 0; i < NPROBE; i++) {
                const uint32_t c0 = clk32();
                if (ping(pr + (i & 7) * 32)) break;
                const uint32_t c1 = clk32();
                if (ping(pr + 1024 + (i & 7) * 32)) break;
                const uint32_t c2 = clk32();
                best[0] = min(best[0], c1 - c0);
                best[1] = min(best[1], c2 - c1);
                if (__any_sync(0xffffffffu, min(best[0], best[1]) < PROBE_FAST || mbar_test(s_kd, 0))) break;
            }
            sel = __shfl_sync(0xffffffffu, best[1] < best[0] ? 4096u : 0u, 0);
            if (lane == 0) sts32(s_tag + 4, sel);
        }
        const uint32_t* const y_src = (const uint32_t*)((uintptr_t)(p.sc->x + xslot(cta >> 2, 2 + j) + lane * 4) ^ sel);
        const uint32_t tag = lds32(s_tag);
        uint32_t n = 0;
        {
            const uint32_t* src = p.sc->ml + ((kvh * 16 + (lane & 15)) * 4 + ((cta >> 2) & 3)) * 2;
            mbar_wait(s_kd, 0);
            uint2 v = ll_ld2(src);
            while (__any_sync(0xffffffffu, bad2(v, tag))) {
                __nanosleep(200);
                if (++n > SPIN_LIMIT) __trap();
                v = ll_ld2(src);
            }
            const float m = untg(v.x), l = untg(v.y);
            float mm = fmaxf(m, __shfl_xor_sync(0xffffffffu, m, 1));
            mm = fmaxf(mm, __shfl_xor_sync(0xffffffffu, mm, 2));
            const float e = ex2((m - mm) * L2E);
            float ll = e * l;
            ll += __shfl_xor_sync(0xffffffffu, ll, 1);
            ll += __shfl_xor_sync(0xffffffffu, ll, 2);
            if (lane < 16) sts32(sb + SM_MISC + 256 + lane * 4, __float_as_uint(__fdividef(e, ll)));
            const uint32_t* hs = p.sc->h + (cta >> 2) * 128 + lane * 4;
#pragma unroll 1
            for (int i = 0; i < (cta < 96 ? 2 : 1); i++) {
                uint4 hv = ll_ld4(hs + i * 32 * 128);
                while (__any_sync(0xffffffffu, bad4(hv, tag))) {
                    __nanosleep(200);
                    if (++n > SPIN_LIMIT) __trap();
                    hv = ll_ld4(hs + i * 32 * 128);
                }
                sts32(sb + SM_H + i * 256 + lane * 8, __byte_perm(hv.x, hv.y, 0x7632));
                sts32(sb + SM_H + i * 256 + lane * 8 + 4, __byte_perm(hv.z, hv.w, 0x7632));
            }
            __syncwarp();
            if (lane == 0) mbar_arrive(s_wrdy, 1);
        }
        auto colsum = [&](float s0, float s1, float s2, float s3) {
            const bool up = lane & 16, mid = lane & 8;
            const float u0 = (up ? s2 : s0) + __shfl_xor_sync(0xffffffffu, up ? s0 : s2, 16);
            const float u1 = (up ? s3 : s1) + __shfl_xor_sync(0xffffffffu, up ? s1 : s3, 16);
            const float u = (mid ? u1 : u0) + __shfl_xor_sync(0xffffffffu, mid ? u0 : u1, 8);
            return rbf(u + __shfl_xor_sync(0xffffffffu, u, 4));
        };
        auto poll32 = [&](uint4 (&a)[4], const uint32_t* src, float& sum) {
            uint32_t bd[4];
#pragma unroll
            for (int i = 0; i < 4; i++) bd[i] = (dif2(a[i].x, a[i].y, tag) | dif2(a[i].z, a[i].w, tag)) & 15u;
            const float s0 = (asf(a[0].x) + asf(a[1].x)) + (asf(a[2].x) + asf(a[3].x)), s1 = (asf(a[0].y) + asf(a[1].y)) + (asf(a[2].y) + asf(a[3].y));
            const float s2 = (asf(a[0].z) + asf(a[1].z)) + (asf(a[2].z) + asf(a[3].z)), s3 = (asf(a[0].w) + asf(a[1].w)) + (asf(a[2].w) + asf(a[3].w));
#pragma unroll
            for (int i = 0; i < 4; i++) ll_ld4_if(a[i], src + i * 128, bd[i]);
            const uint32_t pend = __any_sync(0xffffffffu, (or3(bd[0], bd[1], bd[2]) | bd[3]) != 0);
            sum = colsum(s0, s1, s2, s3);
            return pend;
        };
        uint4 a[4];
        float f, u;
        mbar_wait(s_fd, 0);
#pragma unroll
        for (int i = 0; i < 4; i++) a[i] = ll_ld4(y_src + 512 + i * 128);
        while (poll32(a, y_src + 512, f)) { if (++n > SPIN_LIMIT) __trap(); }
        const float gate = rbf(f * rcp_fast(1.0f + ex2(-f * L2E)));
        __nv_bfloat16* dst = p.out + rb * DM + cg * 16 + ocol;
        PINL(dst);
        mbar_wait(s_vd, 0);
#pragma unroll
        for (int i = 0; i < 4; i++) a[i] = ll_ld4(y_src + i * 128);
        while (true) {
            const uint32_t pend = poll32(a, y_src, u);
            asm volatile("{\n.reg .pred q;\nsetp.eq.u32 q, %2, 0;\n@q st.global.u16 [%0], %1;\n}"
                         :: "l"(dst), "h"(bf_bits(xres + rbf(u * gate))), "r"(pend | (lane & 4)) : "memory");
            if (!pend) break;
            if (++n > SPIN_LIMIT) __trap();
        }
    }
}

typedef CUresult (*EncodeTiledFn)(CUtensorMap*, CUtensorMapDataType, cuuint32_t, void*, const cuuint64_t*, const cuuint64_t*,
                                  const cuuint32_t*, const cuuint32_t*, CUtensorMapInterleave, CUtensorMapSwizzle,
                                  CUtensorMapL2promotion, CUtensorMapFloatOOBfill);

CUtensorMap make_map(EncodeTiledFn enc, const void* base, uint64_t rows, uint64_t cols, uint32_t nblk) {
    CUtensorMap m;
    cuuint64_t gd[3] = {64, rows, cols / 64};
    cuuint64_t gs[2] = {cols * 2, 128};
    cuuint32_t bd[3] = {64, 32, nblk};
    cuuint32_t es[3] = {1, 1, 1};
    enc(&m, CU_TENSOR_MAP_DATA_TYPE_BFLOAT16, 3, const_cast<void*>(base), gd, gs, bd, es, CU_TENSOR_MAP_INTERLEAVE_NONE,
        CU_TENSOR_MAP_SWIZZLE_128B, CU_TENSOR_MAP_L2_PROMOTION_L2_128B, CU_TENSOR_MAP_FLOAT_OOB_FILL_NONE);
    return m;
}

}

extern "C" void kernel_launch(void* const* d_in, const int* in_sizes, int n_in, void* d_out, int out_size) {
    (void)in_sizes; (void)n_in; (void)out_size;
    static EncodeTiledFn enc = nullptr;
    static void* scratch = nullptr;
    if (!enc) {
        void* fn = nullptr;
        cudaDriverEntryPointQueryResult st;
        cudaGetDriverEntryPoint("cuTensorMapEncodeTiled", &fn, cudaEnableDefault, &st);
        enc = (EncodeTiledFn)fn;
        cudaGetSymbolAddress(&scratch, g_scratch);
        cudaFuncSetAttribute(fused_decode_kernel, cudaFuncAttributeMaxDynamicSharedMemorySize, SMEM_BYTES);
    }
    Params p;
    p.x = (const __nv_bfloat16*)d_in[0];
    p.k = (const __nv_bfloat16*)d_in[1];
    p.v = (const __nv_bfloat16*)d_in[2];
    p.wo = (const __nv_bfloat16*)d_in[4];
    p.out = (__nv_bfloat16*)d_out;
    p.sc = (Scratch*)(((uintptr_t)scratch + 65535) & ~(uintptr_t)65535);
    CUtensorMap mwq;
    {
        cuuint64_t gd[2] = {4096, DM};
        cuuint64_t gs[1] = {4096 * 2};
        cuuint32_t bd[2] = {32, 256};
        cuuint32_t es[2] = {1, 1};
        enc(&mwq, CU_TENSOR_MAP_DATA_TYPE_BFLOAT16, 2, d_in[3], gd, gs, bd, es, CU_TENSOR_MAP_INTERLEAVE_NONE,
            CU_TENSOR_MAP_SWIZZLE_64B, CU_TENSOR_MAP_L2_PROMOTION_L2_128B, CU_TENSOR_MAP_FLOAT_OOB_FILL_NONE);
    }
    const CUtensorMap mv = make_map(enc, d_in[2], (uint64_t)NB * HKV * SK, DH, 2);
    const CUtensorMap mwo = make_map(enc, d_in[4], 4096, DM, 2);
    const CUtensorMap mw1 = make_map(enc, d_in[6], DM, DFF, 7);
    const CUtensorMap mw2 = make_map(enc, d_in[7], DFF, DM, 2);
    fused_decode_kernel<<<NCTA, NTHREADS, SMEM_BYTES, cudaStreamPerThread>>>(p, mwq, mv, mwo, mw1, mw2);
}
```
